```python
import torch

def _softmax(x, axis=-1):
    return torch.softmax(x, dim=axis)

def _gelu(x):
    return torch.nn.functional.gelu(x, approximate='tanh')

def _silu(x):
    return torch.nn.functional.silu(x)

def _sigmoid(x):
    return torch.sigmoid(x)

def _layernorm(x, axis=-1, eps=1e-05):
    m = x.mean(dim=axis, keepdim=True)
    v = x.var(dim=axis, keepdim=True, unbiased=False)
    return (x - m) / torch.sqrt(v + eps)

def _scatter_add(tgt, idx, src, axis=0):
    return tgt.clone().index_add_(axis, idx, src)

def _segment_sum(src, seg, n):
    out = torch.zeros((n,) + src.shape[1:], dtype=src.dtype)
    return out.index_add_(0, seg, src)

def _pad(x, pw):
    flat = tuple((v for pair in reversed(pw) for v in pair))
    return torch.nn.functional.pad(x, flat)
kernel_name = 'adaLN_cond__compressed_kv_cla__glu_gated_geglu__decode'

def setup_inputs():

    _w = lambda a: (lambda t: t.to(torch.bfloat16) if t.is_floating_point() else t)(torch.as_tensor(a))

    def _A_setup():
        B, H, Sq, Sk, D, M = (2, 32, 1, 8192, 128, 512)
        Dc = 4 * D
        return {'x': _w((lambda *s: torch.randn(*s, dtype=torch.bfloat16) * 0.05)(B, Sq, M)), 'c_kv': _w((lambda *s: torch.randn(*s, dtype=torch.bfloat16) * 3.2)(B, Sk, Dc)), 'w_q': _w((lambda *s: torch.randn(*s, dtype=torch.bfloat16) * 0.8)(M, H, D) * M ** (-0.5)), 'w_uk': _w((lambda *s: torch.randn(*s, dtype=torch.bfloat16) * 0.8)(Dc, H, D) * Dc ** (-0.5)), 'w_uv': _w((lambda *s: torch.randn(*s, dtype=torch.bfloat16) * 3.2)(Dc, H, D) * Dc ** (-0.5)), 'w_o': _w((lambda *s: torch.randn(*s, dtype=torch.bfloat16) * 3.2)(H, D, M) * (H * D) ** (-0.5))}
    _A_in = _A_setup()

    def _B_setup():
        B, S, Dm, Df = (2, 1, 512, 1792)
        return {'x': _w((lambda *s: torch.randn(*s, dtype=torch.bfloat16) * 0.05)(B, S, Dm)), 'w_gate': _w((lambda *s: torch.randn(*s, dtype=torch.bfloat16) * 3.2)(Dm, Df) * Dm ** (-0.5)), 'w_up': _w((lambda *s: torch.randn(*s, dtype=torch.bfloat16) * 3.2)(Dm, Df) * Dm ** (-0.5)), 'w_down': _w((lambda *s: torch.randn(*s, dtype=torch.bfloat16) * 3.2)(Df, Dm) * Df ** (-0.5))}
    _B_in = _B_setup()
    return {'A_x': _A_in['x'], 'A_c_kv': _A_in['c_kv'], 'A_w_q': _A_in['w_q'], 'A_w_uk': _A_in['w_uk'], 'A_w_uv': _A_in['w_uv'], 'A_w_o': _A_in['w_o'], 'B_x': _B_in['x'], 'B_w_gate': _B_in['w_gate'], 'B_w_up': _B_in['w_up'], 'B_w_down': _B_in['w_down'], 'c': _w((lambda *s: torch.randn(*s, dtype=torch.bfloat16) * 0.1)(2, 512) * 8.0), 'w_mod': _w((lambda *s: torch.randn(*s, dtype=torch.bfloat16) * 0.1)(512, 6 * 512) * 512 ** (-0.5) * 8.0)}

def reference(A_x, A_c_kv, A_w_q, A_w_uk, A_w_uv, A_w_o, B_x, B_w_gate, B_w_up, B_w_down, c, w_mod):

    def _A_ref(x, c_kv, w_q, w_uk, w_uv, w_o):
        B, Sq, M = (x.shape[0], x.shape[1], x.shape[2])
        Sk = c_kv.shape[1]
        H, D = (w_q.shape[1], w_q.shape[2])
        q = torch.einsum('bqm,mhd->bhqd', x, w_q)
        k = torch.einsum('bkc,chd->bhkd', c_kv, w_uk)
        v = torch.einsum('bkc,chd->bhkd', c_kv, w_uv)
        scores = torch.einsum('bhqd,bhkd->bhqk', q, k) * D ** (-0.5)
        off = Sk - Sq
        qi = torch.arange(Sq)[:, None]
        kj = torch.arange(Sk)[None, :]
        cmask = kj <= qi + off
        scores = torch.where(cmask[None, None], scores, -1000000000.0)
        p = _softmax(scores, axis=-1)
        ctx = torch.einsum('bhqk,bhkd->bhqd', p, v)
        return torch.einsum('bhqd,hdm->bqm', ctx, w_o)

    def _B_ref(x, w_gate, w_up, w_down):
        g = torch.einsum('bsd,df->bsf', x, w_gate)
        u = torch.einsum('bsd,df->bsf', x, w_up)
        h = _gelu(g) * u
        return torch.einsum('bsf,fd->bsd', h, w_down)
    x = A_x
    mod = (_silu(c) @ w_mod).reshape(c.shape[0], 6, 1, -1)
    sa, ca, ga, sb, cb, gb = (mod[:, 0].clone(), mod[:, 1].clone(), mod[:, 2].clone(), mod[:, 3].clone(), mod[:, 4].clone(), mod[:, 5].clone())
    h = _layernorm(x, axis=-1) * (1 + ca) + sa
    x = x + ga * _A_ref(h, A_c_kv, A_w_q, A_w_uk, A_w_uv, A_w_o)
    h = _layernorm(x, axis=-1) * (1 + cb) + sb
    x = x + gb * _B_ref(h, B_w_gate, B_w_up, B_w_down)
    return x
```

```cpp
#include <cuda_runtime.h>
#include <cuda_bf16.h>
#include <cuda.h>
#include <stdint.h>

#define D_E0 400
#define D_E1 400
#define D_E2 1500
#define D_X1 400
#define D_X2 400
#define D_E4 450
#define MARK_E2 0
#define ORDER 1
#define PACE_T0 0
#define PACE2_NUM PACE_NUM
#define PACE_NUM 1480

namespace {

constexpr int NCTA = 128;
constexpr int NTHR = 320;
constexpr int NFFN = 112;
#define SPIN_LOG 20
constexpr uint32_t SPIN_LIMIT = 1u << SPIN_LOG;

constexpr int OFF_A = 0;
constexpr int OFF_B = 131072;
constexpr int OFF_C = 163840;
constexpr int OFF_D = 196608;
constexpr int OFF_E = 204800;
constexpr int OFF_M = 221184;
constexpr int OFF_BAR = OFF_M;
constexpr int OFF_SC = OFF_BAR + 256;
constexpr int OFF_ACT = OFF_SC + 2080;
constexpr int OFF_QRED = OFF_ACT + 2080;
constexpr int OFF_CRED = OFF_QRED + 2048;
constexpr int OFF_RED = OFF_CRED + 2048;
constexpr int OFF_SM = OFF_RED + 1024;
constexpr int SMEM_BYTES = OFF_SM + 512;
static_assert(SMEM_BYTES <= 232448, "smem");
constexpr int ACT_PITCH = 1040;
constexpr int ACTL_PITCH = 2064;
constexpr int OFF_WO = OFF_A;
constexpr int OFF_WG = OFF_A + 32768;
constexpr int OFF_WU = OFF_A + 49152;
constexpr int OFF_WD = OFF_A + 65536;
constexpr int OFF_WM2 = OFF_C + 16384;

enum { B_WQ = 0, B_WUK, B_KV0, B_KV1, B_KV2, B_KV3, B_WUV, B_WM2, B_WO, B_WG, B_WU, B_WD,
       B_QRED, B_CRED, B_S0, B_S1, B_S2, B_S3, B_FREEB, B_FREEC, B_FREEA0, B_FREEA1, B_FREEA2, B_PEERC, B_COUNT };

struct __align__(1024) Scratch {
    uint32_t e0[1024];
    uint32_t m2[2048];
    uint32_t x2[4 * 512];
    uint32_t x1[2 * 2 * 2048];
    uint32_t e1[2 * 2 * 2 * 32 * 128];
    uint32_t ml[32 * 2 * 64 * 8];
    uint32_t e4[128 * NFFN * 8];
    uint32_t e2[32 * 4 * 64 * 64];
    uint32_t epoch[32];
};
__device__ Scratch g_s;
#define TLREC(i)
#define TLREC1(i)
#define TLRECP(i)

struct Maps { CUtensorMap wq, wuk, wuv, kv, wo, wm, wg, wu, wd; };

__device__ __forceinline__ uint32_t smem_u32(const void* p) { return (uint32_t)__cvta_generic_to_shared(p); }
__device__ __forceinline__ void mbar_init(uint32_t bar, uint32_t cnt) { asm volatile("mbarrier.init.shared::cta.b64 [%0], %1;" ::"r"(bar), "r"(cnt) : "memory"); }
__device__ __forceinline__ void mbar_expect(uint32_t bar, uint32_t bytes) { asm volatile("mbarrier.arrive.expect_tx.shared::cta.b64 _, [%0], %1;" ::"r"(bar), "r"(bytes) : "memory"); }
__device__ __forceinline__ void mbar_arrive(uint32_t bar) { asm volatile("mbarrier.arrive.shared::cta.b64 _, [%0];" ::"r"(bar) : "memory"); }
__device__ __forceinline__ bool mbar_try(uint32_t bar) {
    uint32_t ok;
    asm volatile("{\n.reg .pred p;\nmbarrier.try_wait.parity.shared::cta.b64 p, [%1], 0;\nselp.u32 %0, 1, 0, p;\n}\n" : "=r"(ok) : "r"(bar) : "memory");
    return ok;
}
__device__ __forceinline__ void mbar_wait(uint32_t bar) { uint32_t n = 0; while (!mbar_try(bar) && ++n < SPIN_LIMIT) {} }
__device__ __forceinline__ bool elect_one() {
    uint32_t p;
    asm volatile("{\n.reg .pred P;\nelect.sync _|P, 0xffffffff;\nselp.u32 %0,1,0,P;\n}\n" : "=r"(p));
    return p;
}
__device__ __forceinline__ void tma2d(uint32_t dst, const CUtensorMap* m, int c0, int c1, uint32_t bar) {
    asm volatile("cp.async.bulk.tensor.2d.shared::cluster.global.mbarrier::complete_tx::bytes [%0], [%1, {%3, %4}], [%2];"
                 ::"r"(dst), "l"(m), "r"(bar), "r"(c0), "r"(c1) : "memory");
}
__device__ __forceinline__ void tma3d(uint32_t dst, const CUtensorMap* m, int c0, int c1, int c2, uint32_t bar) {
    asm volatile("cp.async.bulk.tensor.3d.shared::cluster.global.mbarrier::complete_tx::bytes [%0], [%1, {%3, %4, %5}], [%2];"
                 ::"r"(dst), "l"(m), "r"(bar), "r"(c0), "r"(c1), "r"(c2) : "memory");
}
__device__ __forceinline__ void bar_compute() { asm volatile("bar.sync 1, 256;" ::: "memory"); }
__device__ __forceinline__ uint32_t mapa(uint32_t addr, uint32_t rank) { uint32_t r; asm("mapa.shared::cluster.u32 %0, %1, %2;" : "=r"(r) : "r"(addr), "r"(rank)); return r; }
__device__ __forceinline__ void st_async32(uint32_t addr, float v, uint32_t bar) {
    asm volatile("st.async.weak.shared::cluster.mbarrier::complete_tx::bytes.f32 [%0], %1, [%2];" ::"r"(addr), "f"(v), "r"(bar) : "memory");
}
__device__ __forceinline__ void st_async128(uint32_t addr, float a, float b, float c, float d, uint32_t bar) {
    asm volatile("st.async.weak.shared::cluster.mbarrier::complete_tx::bytes.v4.f32 [%0], {%1,%2,%3,%4}, [%5];" ::"r"(addr), "f"(a), "f"(b), "f"(c), "f"(d), "r"(bar) : "memory");
}
__device__ __forceinline__ uint32_t ldr1(const uint32_t* p) { uint32_t v; asm volatile("ld.relaxed.gpu.global.u32 %0, [%1];" : "=r"(v) : "l"(p) : "memory"); return v; }
__device__ __forceinline__ uint2 ldr2(const uint32_t* p) { uint2 v; asm volatile("ld.relaxed.gpu.global.v2.u32 {%0,%1}, [%2];" : "=r"(v.x), "=r"(v.y) : "l"(p) : "memory"); return v; }
__device__ __forceinline__ uint4 ldr4(const uint32_t* p) { uint4 v; asm volatile("ld.relaxed.gpu.global.v4.u32 {%0,%1,%2,%3}, [%4];" : "=r"(v.x), "=r"(v.y), "=r"(v.z), "=r"(v.w) : "l"(p) : "memory"); return v; }
__device__ __forceinline__ void str1(uint32_t* p, uint32_t v) { asm volatile("st.relaxed.gpu.global.u32 [%0], %1;" ::"l"(p), "r"(v) : "memory"); }
__device__ __forceinline__ void str4(uint32_t* p, uint4 v) { asm volatile("st.relaxed.gpu.global.v4.u32 [%0], {%1,%2,%3,%4};" ::"l"(p), "r"(v.x), "r"(v.y), "r"(v.z), "r"(v.w) : "memory"); }
__device__ __forceinline__ void ldsm4(uint32_t (&r)[4], uint32_t a) { asm volatile("ldmatrix.sync.aligned.m8n8.x4.shared.b16 {%0,%1,%2,%3}, [%4];" : "=r"(r[0]), "=r"(r[1]), "=r"(r[2]), "=r"(r[3]) : "r"(a) : "memory"); }
__device__ __forceinline__ void ldsm4t(uint32_t (&r)[4], uint32_t a) { asm volatile("ldmatrix.sync.aligned.m8n8.x4.trans.shared.b16 {%0,%1,%2,%3}, [%4];" : "=r"(r[0]), "=r"(r[1]), "=r"(r[2]), "=r"(r[3]) : "r"(a) : "memory"); }
__device__ __forceinline__ void stsm4t(uint32_t a, uint32_t r0, uint32_t r1, uint32_t r2, uint32_t r3) { asm volatile("stmatrix.sync.aligned.m8n8.x4.trans.shared.b16 [%0], {%1,%2,%3,%4};" ::"r"(a), "r"(r0), "r"(r1), "r"(r2), "r"(r3) : "memory"); }
__device__ __forceinline__ void mma16816(float (&c)[4], const uint32_t (&a)[4], uint32_t b0, uint32_t b1) {
    asm volatile("mma.sync.aligned.m16n8k16.row.col.f32.bf16.bf16.f32 {%0,%1,%2,%3}, {%4,%5,%6,%7}, {%8,%9}, {%0,%1,%2,%3};"
                 : "+f"(c[0]), "+f"(c[1]), "+f"(c[2]), "+f"(c[3]) : "r"(a[0]), "r"(a[1]), "r"(a[2]), "r"(a[3]), "r"(b0), "r"(b1));
}
__device__ __forceinline__ uint32_t lds32(uint32_t a) { uint32_t v; asm volatile("ld.shared.u32 %0, [%1];" : "=r"(v) : "r"(a) : "memory"); return v; }
__device__ __forceinline__ float ldsf(uint32_t a) { float v; asm volatile("ld.shared.f32 %0, [%1];" : "=f"(v) : "r"(a) : "memory"); return v; }
__device__ __forceinline__ float2 ldsf2(uint32_t a) { float2 v; asm volatile("ld.shared.v2.f32 {%0,%1}, [%2];" : "=f"(v.x), "=f"(v.y) : "r"(a) : "memory"); return v; }
__device__ __forceinline__ float4 ldsf4(uint32_t a) { float4 v; asm volatile("ld.shared.v4.f32 {%0,%1,%2,%3}, [%4];" : "=f"(v.x), "=f"(v.y), "=f"(v.z), "=f"(v.w) : "r"(a) : "memory"); return v; }
__device__ __forceinline__ uint4 lds128(uint32_t a) { uint4 v; asm volatile("ld.shared.v4.u32 {%0,%1,%2,%3}, [%4];" : "=r"(v.x), "=r"(v.y), "=r"(v.z), "=r"(v.w) : "r"(a) : "memory"); return v; }
__device__ __forceinline__ void sts32(uint32_t a, uint32_t v) { asm volatile("st.shared.u32 [%0], %1;" ::"r"(a), "r"(v) : "memory"); }
__device__ __forceinline__ void sts16(uint32_t a, uint16_t v) { asm volatile("st.shared.u16 [%0], %1;" ::"r"(a), "h"(v) : "memory"); }
__device__ __forceinline__ void stsf(uint32_t a, float v) { asm volatile("st.shared.f32 [%0], %1;" ::"r"(a), "f"(v) : "memory"); }
__device__ __forceinline__ void stsf2(uint32_t a, float x, float y) { asm volatile("st.shared.v2.f32 [%0], {%1,%2};" ::"r"(a), "f"(x), "f"(y) : "memory"); }
__device__ __forceinline__ void sts64(uint32_t a, uint32_t x, uint32_t y) { asm volatile("st.shared.v2.u32 [%0], {%1,%2};" ::"r"(a), "r"(x), "r"(y) : "memory"); }
__device__ __forceinline__ void sts128(uint32_t a, uint4 v) { asm volatile("st.shared.v4.u32 [%0], {%1,%2,%3,%4};" ::"r"(a), "r"(v.x), "r"(v.y), "r"(v.z), "r"(v.w) : "memory"); }
__device__ __forceinline__ uint32_t pack2(float lo, float hi) { uint32_t r; asm("cvt.rn.bf16x2.f32 %0, %1, %2;" : "=r"(r) : "f"(hi), "f"(lo)); return r; }
__device__ __forceinline__ float bflo(uint32_t w) { return __uint_as_float(w << 16); }
__device__ __forceinline__ float bfhi(uint32_t w) { return __uint_as_float(w & 0xffff0000u); }
__device__ __forceinline__ uint32_t tagw(uint32_t w, uint32_t tag) { return (w & ~1u) | tag; }
__device__ __forceinline__ bool ok1(uint32_t v, uint32_t tag) { return ((v ^ tag) & 1u) == 0; }
__device__ __forceinline__ bool ok2(uint2 v, uint32_t tag) { return (((v.x ^ tag) | (v.y ^ tag)) & 1u) == 0; }
__device__ __forceinline__ bool ok4(uint4 v, uint32_t tag) { return (((v.x ^ tag) | (v.y ^ tag) | (v.z ^ tag) | (v.w ^ tag)) & 1u) == 0; }
__device__ __forceinline__ float ex2(float x) { float y; asm("ex2.approx.ftz.f32 %0, %1;" : "=f"(y) : "f"(x)); return y; }
__device__ __forceinline__ float warp_sum(float v) {
#pragma unroll
    for (int o = 16; o; o >>= 1) v += __shfl_xor_sync(0xffffffffu, v, o);
    return v;
}
__device__ __forceinline__ uint32_t desclo(uint32_t addr) { return ((addr & 0x3FFFF) >> 4) | (1u << 16); }
template <int TA>
__device__ __forceinline__ void wgmma_n32(float (&d)[16], uint32_t da, uint32_t db, int acc) {
    asm volatile("{\n.reg .pred p;\n.reg .b64 da, db;\nsetp.ne.b32 p, %18, 0;\n"
                 "mov.b64 da, {%16, %20};\nmov.b64 db, {%17, %20};\n"
                 "wgmma.mma_async.sync.aligned.m64n32k16.f32.bf16.bf16 "
                 "{%0,%1,%2,%3,%4,%5,%6,%7,%8,%9,%10,%11,%12,%13,%14,%15}, da, db, p, 1, 1, %19, 0;\n}\n"
                 : "+f"(d[0]), "+f"(d[1]), "+f"(d[2]), "+f"(d[3]), "+f"(d[4]), "+f"(d[5]), "+f"(d[6]), "+f"(d[7]),
                   "+f"(d[8]), "+f"(d[9]), "+f"(d[10]), "+f"(d[11]), "+f"(d[12]), "+f"(d[13]), "+f"(d[14]), "+f"(d[15])
                 : "r"(da), "r"(db), "r"(acc), "n"(TA), "n"(0x40000040));
}
__device__ __forceinline__ void wg_fence() { asm volatile("wgmma.fence.sync.aligned;" ::: "memory"); }
__device__ __forceinline__ void wg_commit() { asm volatile("wgmma.commit_group.sync.aligned;" ::: "memory"); }
__device__ __forceinline__ void wg_wait0() { asm volatile("wgmma.wait_group.sync.aligned 0;" ::: "memory"); }
template <int N>
__device__ __forceinline__ void reg_fence(float (&d)[N]) {
#pragma unroll
    for (int i = 0; i < N; i++) asm volatile("" : "+f"(d[i])::"memory");
}
__device__ __forceinline__ void hold(unsigned t0, unsigned d) { while ((unsigned)clock() - t0 < d) {} }
__device__ __forceinline__ float gelu_tanh(float x) {
    float u = 0.7978845608028654f * (x + 0.044715f * x * x * x);
    float e = __expf(2.f * u);
    float th = 1.f - __fdividef(2.f, e + 1.f);
    return 0.5f * x * (1.f + th);
}

__device__ __forceinline__ void gemv_pair(uint32_t sb, uint32_t wbase, uint32_t red_off, uint32_t bar_idx, int warp, int lane, uint32_t rank) {
    const int mt = warp & 3, kh = warp >> 2, q = lane >> 3, g = lane >> 2, t = lane & 3;
    float c[4] = {0.f, 0.f, 0.f, 0.f};
    const uint32_t ab = sb + OFF_ACT + (g & 1) * ACT_PITCH + t * 4 + kh * 256;
    const int kr = kh * 128 + (q >> 1) * 8 + (lane & 7);
    const uint32_t wa = wbase + kr * 128 + (((2 * mt + (q & 1)) ^ (lane & 7)) << 4);
#pragma unroll
    for (int ks = 0; ks < 8; ks++) {
        uint32_t a[4];
        ldsm4t(a, wa + ks * 2048);
        mma16816(c, a, lds32(ab + ks * 32), lds32(ab + ks * 32 + 16));
    }
    const float v = (t & 2) ? ((t & 1) ? c[3] : c[2]) : ((t & 1) ? c[1] : c[0]);
    const uint32_t off = red_off + (((rank * 2 + kh) * 2 + (t & 1)) * 64 + mt * 16 + (t >> 1) * 8 + g) * 4;
    const uint32_t bar = OFF_BAR + bar_idx * 8;
    st_async32(mapa(sb + off, rank), v, mapa(sb + bar, rank));
    st_async32(mapa(sb + off, rank ^ 1), v, mapa(sb + bar, rank ^ 1));
}

__global__ void __cluster_dims__(2, 1, 1) __launch_bounds__(NTHR, 1)
fused_kernel(const __nv_bfloat16* __restrict__ gx, const __nv_bfloat16* __restrict__ gc,
             const __nv_bfloat16* __restrict__ gwmod, __nv_bfloat16* __restrict__ gout, Scratch* __restrict__ gs,
             const __grid_constant__ Maps maps) {
    extern __shared__ __align__(1024) unsigned char smem[];
    const uint32_t sb = smem_u32(smem);
    const int tid = threadIdx.x, lane = tid & 31;
    const int warp = __shfl_sync(0xffffffffu, tid >> 5, 0);
    const int cta = blockIdx.x;
    const uint32_t rank = cta & 1;
    const int hh = cta >> 2, pp = (cta >> 1) & 1;
    const int ab_ = cta >> 6, kb = (cta >> 1) & 31;
    const int kq = cta >> 5, cg = cta & 31;
    auto BAR = [&](int i) { return sb + OFF_BAR + i * 8; };

    if (warp == 8) {
        if (lane < 9) asm volatile("prefetch.tensormap [%0];" ::"l"(reinterpret_cast<const CUtensorMap*>(&maps) + lane) : "memory");
        if (elect_one()) {
#pragma unroll
            for (int i = B_WQ; i <= B_WD; i++) mbar_init(BAR(i), 1);
            mbar_init(BAR(B_QRED), 1); mbar_init(BAR(B_CRED), 1);
            mbar_init(BAR(B_S0), 1); mbar_init(BAR(B_S1), 1); mbar_init(BAR(B_S2), 1); mbar_init(BAR(B_S3), 1);
            mbar_init(BAR(B_FREEB), 1); mbar_init(BAR(B_FREEC), 8); mbar_init(BAR(B_PEERC), 8);
            mbar_init(BAR(B_FREEA0), 8); mbar_init(BAR(B_FREEA1), 8); mbar_init(BAR(B_FREEA2), 8);
            asm volatile("fence.mbarrier_init.release.cluster;" ::: "memory");
            mbar_expect(BAR(B_WQ), 32768);
            tma2d(sb + OFF_B, &maps.wq, hh * 128 + pp * 64, rank * 256, BAR(B_WQ));
            mbar_expect(BAR(B_QRED), 2048); mbar_expect(BAR(B_CRED), 1024);
            mbar_expect(BAR(B_S0), 8192); mbar_expect(BAR(B_S1), 8192); mbar_expect(BAR(B_S2), 8192); mbar_expect(BAR(B_S3), 8192);
        }
        __syncwarp();
        asm volatile("barrier.cluster.arrive.relaxed.aligned;" ::: "memory");
        if (elect_one()) {
            const unsigned t0 = (unsigned)clock();
            unsigned due = PACE_T0;
            auto pace = [&](unsigned kib) { if (PACE_NUM) { while ((int)((unsigned)clock() - t0 - due) < 0) {} due += kib * PACE_NUM / 16; } };
            auto pace2 = [&](unsigned kib) { if (PACE2_NUM) { while ((int)((unsigned)clock() - t0 - due) < 0) {} due += kib * PACE2_NUM / 16; } };
            auto resync = [&]() { const unsigned now = (unsigned)clock() - t0; if ((int)(now - due) > 0) due = now; };
            auto kvload = [&](int ch) {
                mbar_expect(BAR(B_KV0 + ch), 32768);
                pace(16);
                tma3d(sb + OFF_A + ch * 32768, &maps.kv, 0, ab_ * 8192 + kb * 256 + ch * 64, rank * 4, BAR(B_KV0 + ch));
                pace(16);
                tma3d(sb + OFF_A + ch * 32768 + 16384, &maps.kv, 0, ab_ * 8192 + kb * 256 + ch * 64, rank * 4 + 2, BAR(B_KV0 + ch));
            };
            pace(16);
            tma2d(sb + OFF_B + 16384, &maps.wq, hh * 128 + pp * 64, rank * 256 + 128, BAR(B_WQ));
            mbar_expect(BAR(B_WUK), 32768);
            pace(16);
            tma2d(sb + OFF_C, &maps.wuk, hh * 128 + pp * 64, rank * 256, BAR(B_WUK));
            pace(16);
            tma2d(sb + OFF_C + 16384, &maps.wuk, hh * 128 + pp * 64, rank * 256 + 128, BAR(B_WUK));
            kvload(0);
            kvload(1);
            kvload(2);
            if (ORDER == 0) kvload(3);
            TLRECP(20);
            mbar_wait(BAR(B_FREEB));
            resync();
            mbar_expect(BAR(B_WUV), 32768);
            pace(16);
            tma2d(sb + OFF_B, &maps.wuv, hh * 128, (cta & 3) * 128, BAR(B_WUV));
            pace(16);
            tma2d(sb + OFF_B + 16384, &maps.wuv, hh * 128 + 64, (cta & 3) * 128, BAR(B_WUV));
            mbar_wait(BAR(B_FREEC));
            resync();
            mbar_expect(BAR(B_WM2), 16384);
            pace(16);
            tma2d(sb + OFF_WM2, &maps.wm, 1024 + cta * 16, 0, BAR(B_WM2));
            tma2d(sb + OFF_WM2 + 8192, &maps.wm, 1024 + cta * 16, 256, BAR(B_WM2));
            if (ORDER == 1) kvload(3);
            TLRECP(21);
            mbar_wait(BAR(B_FREEA0));
            resync();
            TLRECP(22);
            mbar_expect(BAR(B_WO), 32768);
            pace2(16);
            tma2d(sb + OFF_WO, &maps.wo, cg * 16, kq * 1024, BAR(B_WO));
            tma2d(sb + OFF_WO + 8192, &maps.wo, cg * 16, kq * 1024 + 256, BAR(B_WO));
            pace2(16);
            tma2d(sb + OFF_WO + 16384, &maps.wo, cg * 16, kq * 1024 + 512, BAR(B_WO));
            tma2d(sb + OFF_WO + 24576, &maps.wo, cg * 16, kq * 1024 + 768, BAR(B_WO));
            if (ORDER == 2) kvload(3);
            if (cta < NFFN) {
                mbar_wait(BAR(B_FREEA1));
                resync();
                mbar_expect(BAR(B_WG), 16384);
                pace2(16);
                tma2d(sb + OFF_WG, &maps.wg, cta * 16, 0, BAR(B_WG));
                tma2d(sb + OFF_WG + 8192, &maps.wg, cta * 16, 256, BAR(B_WG));
                mbar_expect(BAR(B_WU), 16384);
                pace2(16);
                tma2d(sb + OFF_WU, &maps.wu, cta * 16, 0, BAR(B_WU));
                tma2d(sb + OFF_WU + 8192, &maps.wu, cta * 16, 256, BAR(B_WU));
            }
            if (ORDER == 3) kvload(3);
            TLRECP(23);
            if (cta < NFFN) {
                mbar_wait(BAR(B_FREEA2));
                resync();
                mbar_expect(BAR(B_WD), 16384);
                pace2(16);
                tma3d(sb + OFF_WD, &maps.wd, 0, cta * 16, 0, BAR(B_WD));
            }
            TLRECP(24);
        }
        __syncwarp();
        asm volatile("barrier.cluster.wait.aligned;" ::: "memory");
        return;
    }

    const uint32_t epoch = ldr1(gs->epoch);

    if (warp == 9) {
        asm volatile("barrier.cluster.arrive.relaxed.aligned;" ::: "memory");
        const uint32_t tag = (epoch + 1) & 1, inv = tag ^ 1;
        const uint4 iv = make_uint4(inv, inv, inv, inv);
        if (lane < 2) str4(gs->e0 + cta * 8 + lane * 4, iv);
        {
            uint32_t* e1 = gs->e1 + ((rank * 2 + pp) * 32 + hh) * 128;
            str4(e1 + lane * 4, iv);
            str4(e1 + 4 * 32 * 128 + lane * 4, iv);
        }
        asm volatile("bar.sync 2, 288;" ::: "memory");
        {
#pragma unroll
            for (int j = 0; j < 2; j++) {
                const int u = j * 32 + lane;
                str4(gs->ml + (((u >> 1) * 2 + rank) * 64 + ab_ * 32 + kb) * 8 + (u & 1) * 4, iv);
            }
            if (lane < 16) str4(gs->x1 + (pp * 2 + rank) * 2048 + hh * 64 + lane * 4, iv);
            else if (lane < 20) str4(gs->x2 + kq * 512 + cg * 16 + (lane - 16) * 4, iv);
            else if (lane < 24) str4(gs->m2 + cta * 16 + (lane - 20) * 4, iv);
            if (cta < NFFN) {
#pragma unroll 2
                for (int j = 0; j < 8; j++) {
                    const int u = j * 32 + lane;
                    str4(gs->e4 + ((u >> 1) * NFFN + cta) * 8 + (u & 1) * 4, iv);
                }
            }
        }
        asm volatile("barrier.cluster.wait.aligned;" ::: "memory");
        asm volatile("bar.sync 3, 288;" ::: "memory");
        mbar_wait(BAR(B_WM2));
        const int q = lane >> 3, g = lane >> 2, t = lane & 3;
        float c0[4] = {0.f, 0.f, 0.f, 0.f}, c1[4] = {0.f, 0.f, 0.f, 0.f};
        const uint32_t ab = sb + OFF_SC + (g & 1) * ACT_PITCH + t * 4;
        const int kr = (q >> 1) * 8 + (lane & 7);
        const uint32_t wa = sb + OFF_WM2 + kr * 32 + ((((q & 1)) ^ ((kr >> 2) & 1)) << 4);
#pragma unroll 4
        for (int ks = 0; ks < 32; ks += 2) {
            uint32_t a[4], a2[4];
            ldsm4t(a, wa + ks * 512);
            ldsm4t(a2, wa + ks * 512 + 512);
            mma16816(c0, a, lds32(ab + ks * 32), lds32(ab + ks * 32 + 16));
            mma16816(c1, a2, lds32(ab + ks * 32 + 32), lds32(ab + ks * 32 + 48));
        }
        if (t < 2) {
            const uint32_t w = t ? pack2(c0[2] + c1[2], c0[3] + c1[3]) : pack2(c0[0] + c1[0], c0[1] + c1[1]);
            str1(gs->m2 + cta * 16 + t * 8 + g, tagw(w, tag));
        }
        return;
    }

    const int q4 = lane >> 3, g = lane >> 2, t = lane & 3;
    {
        const __nv_bfloat16* src = gwmod + (size_t)tid * 3072 + cta * 8;
        asm volatile("cp.async.cg.shared.global [%0], [%1], 16;" ::"r"(sb + OFF_D + tid * 16), "l"(src) : "memory");
        asm volatile("cp.async.cg.shared.global [%0], [%1], 16;" ::"r"(sb + OFF_D + 4096 + tid * 16), "l"(src + 256 * 3072) : "memory");
        asm volatile("cp.async.commit_group;" ::: "memory");
    }
    const uint32_t xw0 = __ldg(reinterpret_cast<const uint32_t*>(gx) + tid);
    const uint32_t xw1 = __ldg(reinterpret_cast<const uint32_t*>(gx) + 256 + tid);
    const float xh0 = __bfloat162float(gx[rank * 256 + tid]), xh1 = __bfloat162float(gx[512 + rank * 256 + tid]);
    {
        const uint32_t cw0 = __ldg(reinterpret_cast<const uint32_t*>(gc) + tid);
        const uint32_t cw1 = __ldg(reinterpret_cast<const uint32_t*>(gc) + 256 + tid);
        auto silu = [](float v) { return __fdividef(v, 1.f + __expf(-v)); };
        sts32(sb + OFF_SC + tid * 4, pack2(silu(bflo(cw0)), silu(bfhi(cw0))));
        sts32(sb + OFF_SC + ACT_PITCH + tid * 4, pack2(silu(bflo(cw1)), silu(bfhi(cw1))));
        float s0 = bflo(xw0) + bfhi(xw0), s1 = bflo(xw1) + bfhi(xw1);
        s0 = warp_sum(s0); s1 = warp_sum(s1);
        if (lane == 0) stsf2(sb + OFF_SM + warp * 8, s0, s1);
        if (tid < 32) { sts32(sb + OFF_SM + 256 + tid * 4, 0x80000000u); sts32(sb + OFF_SM + 384 + tid * 4, 0u); }
    }
    asm volatile("barrier.cluster.arrive.relaxed.aligned;" ::: "memory");
    asm volatile("cp.async.wait_group 0;" ::: "memory");
    asm volatile("bar.sync 2, 288;" ::: "memory");
    const uint32_t tag = (epoch + 1) & 1;
    TLREC(0);
    float mean0 = 0.f, mean1 = 0.f;
    {
#pragma unroll
        for (int w = 0; w < 8; w++) { float2 v = ldsf2(sb + OFF_SM + w * 8); mean0 += v.x; mean1 += v.y; }
        mean0 *= (1.f / 512.f); mean1 *= (1.f / 512.f);
        float c[4] = {0.f, 0.f, 0.f, 0.f};
        const uint32_t aa = sb + OFF_SC + (g & 1) * ACT_PITCH + warp * 128 + t * 4;
#pragma unroll
        for (int j = 0; j < 2; j++) {
            uint32_t b[4];
            ldsm4t(b, sb + OFF_D + (warp * 64 + j * 32 + lane) * 16);
            uint32_t a[4];
            a[0] = lds32(aa + j * 64); a[2] = lds32(aa + j * 64 + 16); a[1] = 0; a[3] = 0;
            mma16816(c, a, b[0], b[1]);
            a[0] = lds32(aa + j * 64 + 32); a[2] = lds32(aa + j * 64 + 48);
            mma16816(c, a, b[2], b[3]);
        }
        if (g < 2) stsf2(sb + OFF_RED + ((warp * 2 + g) * 8 + 2 * t) * 4, c[0], c[1]);
        float d0 = bflo(xw0) - mean0, d1 = bfhi(xw0) - mean0, d2 = bflo(xw1) - mean1, d3 = bfhi(xw1) - mean1;
        float v0 = warp_sum(d0 * d0 + d1 * d1), v1 = warp_sum(d2 * d2 + d3 * d3);
        if (lane == 0) stsf2(sb + OFF_SM + 64 + warp * 8, v0, v1);
    }
    bar_compute();
    if (tid < 8) {
        float s0 = 0.f, s1 = 0.f;
#pragma unroll
        for (int w = 0; w < 8; w++) { s0 += ldsf(sb + OFF_RED + (w * 16 + tid) * 4); s1 += ldsf(sb + OFF_RED + (w * 16 + 8 + tid) * 4); }
        str1(gs->e0 + cta * 8 + tid, tagw(pack2(s0, s1), tag));
    }
    TLREC(1);
    {
        const unsigned tw0 = (unsigned)clock();
        float v0 = 0.f, v1 = 0.f;
#pragma unroll
        for (int w = 0; w < 8; w++) { float2 v = ldsf2(sb + OFF_SM + 64 + w * 8); v0 += v.x; v1 += v.y; }
        const float r0 = rsqrtf(v0 * (1.f / 512.f) + 1e-5f), r1 = rsqrtf(v1 * (1.f / 512.f) + 1e-5f);
        const uint32_t* ps = gs->e0 + rank * 256 + tid;
        uint32_t sa, ca, n = 0;
        hold(tw0, D_E0);
        do { sa = ldr1(ps); ca = ldr1(ps + 512); } while (!(ok1(sa, tag) && ok1(ca, tag)) && ++n < SPIN_LIMIT);
        const float h0 = (xh0 - mean0) * r0 * (1.f + bflo(ca)) + bflo(sa);
        const float h1 = (xh1 - mean1) * r1 * (1.f + bfhi(ca)) + bfhi(sa);
        const uint32_t hw = pack2(h0, h1);
        sts16(sb + OFF_ACT + tid * 2, (uint16_t)(hw & 0xffff));
        sts16(sb + OFF_ACT + ACT_PITCH + tid * 2, (uint16_t)(hw >> 16));
    }
    asm volatile("barrier.cluster.wait.aligned;" ::: "memory");
    bar_compute();
    TLREC(2);
    mbar_wait(BAR(B_WQ));
    TLREC(3);
    gemv_pair(sb, sb + OFF_B, OFF_QRED, B_QRED, warp, lane, rank);
    mbar_wait(BAR(B_QRED));
    if (tid == 0) mbar_arrive(BAR(B_FREEB));
    if (tid < 64) {
        const int b = tid >> 5, k2 = tid & 31;
        float s0 = 0.f, s1 = 0.f;
#pragma unroll
        for (int s = 0; s < 4; s++) { float2 v = ldsf2(sb + OFF_QRED + ((s * 2 + b) * 64 + 2 * k2) * 4); s0 += v.x; s1 += v.y; }
        sts32(sb + OFF_ACT + b * ACT_PITCH + k2 * 4, pack2(s0, s1));
    }
    bar_compute();
    TLREC(4);
    mbar_wait(BAR(B_WUK));
    TLREC(5);
    {
        uint32_t bf[8];
        const uint32_t ab = sb + OFF_ACT + (g & 1) * ACT_PITCH + t * 4;
#pragma unroll
        for (int ks = 0; ks < 4; ks++) { bf[2 * ks] = lds32(ab + ks * 32); bf[2 * ks + 1] = lds32(ab + ks * 32 + 16); }
#pragma unroll
        for (int mi = 0; mi < 2; mi++) {
            const int m = (warp * 2 + mi) * 16 + (q4 & 1) * 8 + (lane & 7);
            float c[4] = {0.f, 0.f, 0.f, 0.f};
#pragma unroll
            for (int ks = 0; ks < 4; ks++) {
                uint32_t a[4];
                ldsm4(a, sb + OFF_C + m * 128 + (((2 * ks + (q4 >> 1)) ^ (lane & 7)) << 4));
                mma16816(c, a, bf[2 * ks], bf[2 * ks + 1]);
            }
            const float v = (t & 2) ? ((t & 1) ? c[3] : c[2]) : ((t & 1) ? c[1] : c[0]);
            const uint32_t w = pack2(v, 0.f);
            sts16(sb + OFF_RED + (t & 1) * 512 + ((warp * 2 + mi) * 16 + (t >> 1) * 8 + g) * 2, (uint16_t)(w & 0xffff));
        }
    }
    __syncwarp();
    if (lane == 0) {
        mbar_arrive(BAR(B_FREEC));
        asm volatile("mbarrier.arrive.relaxed.cluster.shared::cluster.b64 _, [%0];" ::"r"(mapa(BAR(B_PEERC), rank ^ 1)) : "memory");
    }
    if (lane < 8) {
        const int b = lane >> 2;
        uint4 v = lds128(sb + OFF_RED + b * 512 + warp * 64 + (lane & 3) * 16);
        v.x = tagw(v.x, tag); v.y = tagw(v.y, tag); v.z = tagw(v.z, tag); v.w = tagw(v.w, tag);
        str4(gs->e1 + (((b * 2 + rank) * 2 + pp) * 32 + hh) * 128 + warp * 16 + (lane & 3) * 4, v);
    }
    TLREC(6);
    {
        const uint32_t* base = gs->e1 + ((ab_ * 2 + rank) * 2) * 32 * 128 + warp * 4 * 128;
        hold((unsigned)clock(), D_E1);
        {
            const uint32_t* pr = base + ((lane >> 2) & 1) * 32 * 128 + (lane >> 3) * 128 + (lane & 3) * 32 + 28;
            uint32_t n = 0;
            bool ok;
            do { ok = ok4(ldr4(pr), tag); } while (!__all_sync(0xffffffffu, ok) && ++n < SPIN_LIMIT);
        }
        uint4 v[8];
        uint32_t n = 0;
        bool ok;
        do {
#pragma unroll
            for (int j = 0; j < 8; j++) v[j] = ldr4(base + (j & 1) * 32 * 128 + (j >> 1) * 128 + lane * 4);
            ok = true;
#pragma unroll
            for (int j = 0; j < 8; j++) ok = ok && ok4(v[j], tag);
        } while (!ok && ++n < SPIN_LIMIT);
#pragma unroll
        for (int j = 0; j < 4; j++) {
            const uint4 a = v[2 * j], b = v[2 * j + 1];
            uint4 o;
            o.x = pack2(bflo(a.x) + bflo(b.x), bfhi(a.x) + bfhi(b.x));
            o.y = pack2(bflo(a.y) + bflo(b.y), bfhi(a.y) + bfhi(b.y));
            o.z = pack2(bflo(a.z) + bflo(b.z), bfhi(a.z) + bfhi(b.z));
            o.w = pack2(bflo(a.w) + bflo(b.w), bfhi(a.w) + bfhi(b.w));
            const int head = warp * 4 + j;
            sts128(sb + OFF_E + (lane >> 3) * 4096 + head * 128 + (((lane & 7) ^ (head & 7)) << 4), o);
        }
    }
    asm volatile("fence.proxy.async.shared::cta;" ::: "memory");
    mbar_wait(BAR(B_PEERC));
    asm volatile("bar.sync 3, 288;" ::: "memory");
    TLREC(7);
    const int wg = warp >> 2, wi = warp & 3, tw = tid & 127;
    {
        constexpr float SC = 0.08838834764831845f * 1.4426950408889634f;
        float o0[16], o1[16], lsum[8], mold[8];
        const uint32_t dA = desclo(sb + OFF_A), dD = desclo(sb + OFF_D), dE = desclo(sb + OFF_E);
#pragma unroll
        for (int i = 0; i < 8; i++) { lsum[i] = 0.f; mold[i] = -3.0e38f; }
#pragma unroll
        for (int i = 0; i < 16; i++) { o0[i] = 0.f; o1[i] = 0.f; }
#pragma unroll 1
        for (int s = 0; s < 4; s++) {
            const bool own = (s & 1) == wg;
            float sacc[16];
            mbar_wait(BAR(B_KV0 + s));
            TLREC(8 + (s == 2) * 2);
            if (own) {
                wg_fence();
#pragma unroll
                for (int cb = 0; cb < 4; cb++)
#pragma unroll
                    for (int ks = 0; ks < 4; ks++)
                        wgmma_n32<0>(sacc, dA + s * 2048 + cb * 512 + ks * 2, dE + cb * 256 + ks * 2, (cb | ks) != 0);
                wg_commit();
                wg_wait0();
                reg_fence(sacc);
                TLREC1(26);
                const uint32_t so = OFF_C + wg * 8192 + tw * 16;
                const uint32_t ra = mapa(sb + so, rank ^ 1), rb = mapa(BAR(B_S0 + s), rank ^ 1);
#pragma unroll
                for (int j = 0; j < 4; j++) st_async128(ra + j * 2048, sacc[4 * j], sacc[4 * j + 1], sacc[4 * j + 2], sacc[4 * j + 3], rb);
                mbar_wait(BAR(B_S0 + s));
#pragma unroll
                for (int j = 0; j < 4; j++) {
                    const float4 p = ldsf4(sb + so + j * 2048);
                    sacc[4 * j] = (sacc[4 * j] + p.x) * SC; sacc[4 * j + 1] = (sacc[4 * j + 1] + p.y) * SC;
                    sacc[4 * j + 2] = (sacc[4 * j + 2] + p.z) * SC; sacc[4 * j + 3] = (sacc[4 * j + 3] + p.w) * SC;
                }
                TLREC1(27);
                float mx[8];
#pragma unroll
                for (int j = 0; j < 4; j++) { mx[2 * j] = fmaxf(sacc[4 * j], sacc[4 * j + 2]); mx[2 * j + 1] = fmaxf(sacc[4 * j + 1], sacc[4 * j + 3]); }
                const bool u4 = lane & 16, u2 = lane & 8, u1 = lane & 4;
                float y[4], z[2];
#pragma unroll
                for (int i = 0; i < 4; i++) { const float keep = u4 ? mx[i + 4] : mx[i], send = u4 ? mx[i] : mx[i + 4]; y[i] = fmaxf(keep, __shfl_xor_sync(0xffffffffu, send, 16)); }
#pragma unroll
                for (int i = 0; i < 2; i++) { const float keep = u2 ? y[i + 2] : y[i], send = u2 ? y[i] : y[i + 2]; z[i] = fmaxf(keep, __shfl_xor_sync(0xffffffffu, send, 8)); }
                const float keep = u1 ? z[1] : z[0], send = u1 ? z[0] : z[1];
                const float r = fmaxf(keep, __shfl_xor_sync(0xffffffffu, send, 4));
                int key = __float_as_int(r);
                key = key >= 0 ? key : key ^ 0x7fffffff;
                const int head = 8 * (g >> 1) + 2 * t + (g & 1);
                asm volatile("red.shared.max.s32 [%0], %1;" ::"r"(sb + OFF_SM + 256 + head * 4), "r"(key) : "memory");
            }
            bar_compute();
            TLREC1(28);
            float mnew[8], alpha[8];
#pragma unroll
            for (int j = 0; j < 4; j++) {
                const float2 kk = ldsf2(sb + OFF_SM + 256 + (8 * j + 2 * t) * 4);
                int k0 = __float_as_int(kk.x), k1 = __float_as_int(kk.y);
                k0 = k0 >= 0 ? k0 : k0 ^ 0x7fffffff; k1 = k1 >= 0 ? k1 : k1 ^ 0x7fffffff;
                mnew[2 * j] = __int_as_float(k0); mnew[2 * j + 1] = __int_as_float(k1);
            }
            if (own) {
                uint32_t pk[8];
#pragma unroll
                for (int j = 0; j < 4; j++) {
                    const float p0 = ex2(sacc[4 * j] - mnew[2 * j]), p1 = ex2(sacc[4 * j + 1] - mnew[2 * j + 1]);
                    const float p2 = ex2(sacc[4 * j + 2] - mnew[2 * j]), p3 = ex2(sacc[4 * j + 3] - mnew[2 * j + 1]);
                    pk[2 * j] = pack2(p0, p1); pk[2 * j + 1] = pack2(p2, p3);
                }
                const int hrow = (q4 >> 1) * 8 + (lane & 7);
                const uint32_t pa = sb + OFF_D + wg * 4096 + hrow * 128 + (((2 * wi + (q4 & 1)) ^ (lane & 7)) << 4);
                stsm4t(pa, pk[0], pk[1], pk[2], pk[3]);
                stsm4t(pa + 2048, pk[4], pk[5], pk[6], pk[7]);
                asm volatile("fence.proxy.async.shared::cta;" ::: "memory");
#pragma unroll
                for (int j = 0; j < 4; j++) {
                    sacc[2 * j] = bflo(pk[2 * j]) + bflo(pk[2 * j + 1]);
                    sacc[2 * j + 1] = bfhi(pk[2 * j]) + bfhi(pk[2 * j + 1]);
                }
            } else {
#pragma unroll
                for (int i = 0; i < 8; i++) sacc[i] = 0.f;
            }
#pragma unroll
            for (int i = 0; i < 8; i++) { alpha[i] = ex2(mold[i] - mnew[i]); mold[i] = mnew[i]; lsum[i] = lsum[i] * alpha[i] + sacc[i]; }
#pragma unroll
            for (int j = 0; j < 4; j++) {
                o0[4 * j] *= alpha[2 * j]; o0[4 * j + 1] *= alpha[2 * j + 1]; o0[4 * j + 2] *= alpha[2 * j]; o0[4 * j + 3] *= alpha[2 * j + 1];
                o1[4 * j] *= alpha[2 * j]; o1[4 * j + 1] *= alpha[2 * j + 1]; o1[4 * j + 2] *= alpha[2 * j]; o1[4 * j + 3] *= alpha[2 * j + 1];
            }
            bar_compute();
            TLREC1(29);
            wg_fence();
#pragma unroll
            for (int ks = 0; ks < 4; ks++) {
                const uint32_t ka = dA + s * 2048 + wg * 1024 + ks * 128;
                const uint32_t db = dD + (s & 1) * 256 + ks * 2;
                wgmma_n32<1>(o0, ka, db, 1);
                wgmma_n32<1>(o1, ka + 512, db, 1);
            }
            wg_commit();
            if (s == 3) {
                const bool u4 = lane & 16, u2 = lane & 8, u1 = lane & 4;
                float y[4], z[2];
#pragma unroll
                for (int i = 0; i < 4; i++) { const float keep = u4 ? lsum[i + 4] : lsum[i], send = u4 ? lsum[i] : lsum[i + 4]; y[i] = keep + __shfl_xor_sync(0xffffffffu, send, 16); }
#pragma unroll
                for (int i = 0; i < 2; i++) { const float keep = u2 ? y[i + 2] : y[i], send = u2 ? y[i] : y[i + 2]; z[i] = keep + __shfl_xor_sync(0xffffffffu, send, 8); }
                const float keep = u1 ? z[1] : z[0], send = u1 ? z[0] : z[1];
                const float r = keep + __shfl_xor_sync(0xffffffffu, send, 4);
                const int head = 8 * (g >> 1) + 2 * t + (g & 1);
                asm volatile("red.shared.add.f32 [%0], %1;" ::"r"(sb + OFF_SM + 384 + head * 4), "f"(r) : "memory");
            }
            wg_wait0();
            reg_fence(o0); reg_fence(o1);
            if (s < 3 && lane == 0) mbar_arrive(BAR(B_FREEA0 + s));
            TLREC(9 + (s == 2) * 21);
        }
        TLREC(31);
        {
            const int hrow = (q4 >> 1) * 8 + (lane & 7);
#pragma unroll
            for (int mi = 0; mi < 2; mi++) {
                const float(&o)[16] = mi ? o1 : o0;
                const int chunk = (wg * 2 + mi) * 8 + wi * 2 + (q4 & 1);
                const uint32_t a = sb + OFF_E + hrow * 512 + ((chunk ^ (lane & 7)) << 4);
                stsm4t(a, pack2(o[0], o[1]), pack2(o[2], o[3]), pack2(o[4], o[5]), pack2(o[6], o[7]));
                stsm4t(a + 16 * 512, pack2(o[8], o[9]), pack2(o[10], o[11]), pack2(o[12], o[13]), pack2(o[14], o[15]));
            }
        }
    }
    bar_compute();
    TLREC(11);
    {
        const int part = ab_ * 32 + kb;
#pragma unroll
        for (int j = 0; j < 4; j++) {
            const int head = warp * 4 + j;
            uint4 v = lds128(sb + OFF_E + head * 512 + ((lane ^ (head & 7)) << 4));
            v.x = tagw(v.x, tag); v.y = tagw(v.y, tag); v.z = tagw(v.z, tag); v.w = tagw(v.w, tag);
            str4(gs->e2 + ((head * 4 + rank * 2 + (lane >> 4)) * 64 + part) * 64 + (lane & 15) * 4, v);
        }
        if (lane < 8) {
            const int head = warp * 4 + (lane >> 1);
            int k = (int)lds32(sb + OFF_SM + 256 + head * 4);
            k = k >= 0 ? k : k ^ 0x7fffffff;
            const uint32_t m = tagw((uint32_t)k, tag), l = tagw(lds32(sb + OFF_SM + 384 + head * 4), tag);
            str4(gs->ml + ((head * 2 + rank) * 64 + part) * 8 + (lane & 1) * 4, make_uint4(m, l, m, l));
        }
    }
    TLREC(12);
    {
        const unsigned tw0 = (unsigned)clock();
        const int b = warp >> 2;
        const uint32_t* pml = gs->ml + ((hh * 2 + pp) * 64 + b * 32 + lane) * 8;
        const uint32_t* pd = gs->e2 + ((hh * 4 + (cta & 3)) * 64 + b * 32 + g) * 64 + (warp & 3) * 16 + t * 4;
        uint2 ml = make_uint2(~tag, ~tag);
        uint4 v[4];
#pragma unroll
        for (int j = 0; j < 4; j++) v[j] = make_uint4(~tag, ~tag, ~tag, ~tag);
        hold(tw0, D_E2);
        uint32_t n = 0;
        bool ok;
        do {
            if (!ok2(ml, tag)) ml = ldr2(pml);
#pragma unroll
            for (int j = 0; j < 4; j++) if (!ok4(v[j], tag)) v[j] = ldr4(pd + j * 8 * 64);
            ok = ok2(ml, tag) && ok4(v[0], tag) && ok4(v[1], tag) && ok4(v[2], tag) && ok4(v[3], tag);
        } while (!ok && ++n < SPIN_LIMIT);
        __syncwarp();
        const float m = __uint_as_float(ml.x);
        float M = m;
#pragma unroll
        for (int o = 16; o; o >>= 1) M = fmaxf(M, __shfl_xor_sync(0xffffffffu, M, o));
        float w = ex2(m - M);
        const float L = warp_sum(w * __uint_as_float(ml.y));
        w = __fdividef(w, L);
        float a[8];
#pragma unroll
        for (int i = 0; i < 8; i++) a[i] = 0.f;
#pragma unroll
        for (int j = 0; j < 4; j++) {
            const float wj = __shfl_sync(0xffffffffu, w, j * 8 + g);
            a[0] += wj * bflo(v[j].x); a[1] += wj * bfhi(v[j].x); a[2] += wj * bflo(v[j].y); a[3] += wj * bfhi(v[j].y);
            a[4] += wj * bflo(v[j].z); a[5] += wj * bfhi(v[j].z); a[6] += wj * bflo(v[j].w); a[7] += wj * bfhi(v[j].w);
        }
        const bool u4 = lane & 16, u2 = lane & 8;
        float y[4], z[2];
#pragma unroll
        for (int i = 0; i < 4; i++) { const float keep = u4 ? a[i + 4] : a[i], send = u4 ? a[i] : a[i + 4]; y[i] = keep + __shfl_xor_sync(0xffffffffu, send, 16); }
#pragma unroll
        for (int i = 0; i < 2; i++) { const float keep = u2 ? y[i + 2] : y[i], send = u2 ? y[i] : y[i + 2]; z[i] = keep + __shfl_xor_sync(0xffffffffu, send, 8); }
        z[0] += __shfl_xor_sync(0xffffffffu, z[0], 4); z[1] += __shfl_xor_sync(0xffffffffu, z[1], 4);
        if (!(lane & 4)) sts32(sb + OFF_ACT + b * ACT_PITCH + ((warp & 3) * 32 + t * 8 + (g >> 1) * 2) * 2, pack2(z[0], z[1]));
    }
    uint2 ga = ldr2(gs->m2 + 2 * tid), sbv = ldr2(gs->m2 + 512 + 2 * tid), cbv = ldr2(gs->m2 + 1024 + 2 * tid);
    uint32_t gbw = ldr1(gs->m2 + 1536 + (cta & 63) * 8 + (tid & 7));
    bar_compute();
    TLREC(13);
    mbar_wait(BAR(B_WUV));
    {
        float c[4] = {0.f, 0.f, 0.f, 0.f};
        const uint32_t ab = sb + OFF_ACT + (g & 1) * ACT_PITCH + t * 4;
        const int kr = (q4 >> 1) * 8 + (lane & 7);
        const uint32_t wa = sb + OFF_B + (warp >> 2) * 16384 + kr * 128 + (((2 * (warp & 3) + (q4 & 1)) ^ (lane & 7)) << 4);
        float c2[4] = {0.f, 0.f, 0.f, 0.f};
#pragma unroll
        for (int ks = 0; ks < 8; ks += 2) {
            uint32_t a[4], a2[4];
            ldsm4t(a, wa + ks * 2048);
            ldsm4t(a2, wa + ks * 2048 + 2048);
            mma16816(c, a, lds32(ab + ks * 32), lds32(ab + ks * 32 + 16));
            mma16816(c2, a2, lds32(ab + ks * 32 + 32), lds32(ab + ks * 32 + 48));
        }
        const float v = (t & 2) ? ((t & 1) ? c[3] + c2[3] : c[2] + c2[2]) : ((t & 1) ? c[1] + c2[1] : c[0] + c2[0]);
        st_async32(mapa(sb + OFF_CRED + (rank * 128 + warp * 16 + (t >> 1) * 8 + g) * 4, t & 1), v, mapa(BAR(B_CRED), t & 1));
    }
    if (warp < 2) {
        mbar_wait(BAR(B_CRED));
        const float2 u = ldsf2(sb + OFF_CRED + tid * 8), v = ldsf2(sb + OFF_CRED + 512 + tid * 8);
        str1(gs->x1 + (pp * 2 + rank) * 2048 + hh * 64 + tid, tagw(pack2(u.x + v.x, u.y + v.y), tag));
    }
    TLREC(14);
    {
        const unsigned tw0 = (unsigned)clock();
        const uint32_t* px = gs->x1 + (tid >> 7) * 2048 + kq * 512 + (tid & 127) * 4;
        uint4 u, v;
        uint32_t n = 0;
        hold(tw0, warp < 2 ? D_X1 : D_X1 + 300);
        do { u = ldr4(px); v = ldr4(px + 4096); } while (!(ok4(u, tag) && ok4(v, tag)) && ++n < SPIN_LIMIT);
        uint4 o;
        o.x = pack2(bflo(u.x) + bflo(v.x), bfhi(u.x) + bfhi(v.x));
        o.y = pack2(bflo(u.y) + bflo(v.y), bfhi(u.y) + bfhi(v.y));
        o.z = pack2(bflo(u.z) + bflo(v.z), bfhi(u.z) + bfhi(v.z));
        o.w = pack2(bflo(u.w) + bflo(v.w), bfhi(u.w) + bfhi(v.w));
        sts128(sb + OFF_D + (tid >> 7) * ACTL_PITCH + (tid & 127) * 16, o);
    }
    bar_compute();
    TLREC(15);
    mbar_wait(BAR(B_WO));
    {
        float c[4] = {0.f, 0.f, 0.f, 0.f}, c2[4] = {0.f, 0.f, 0.f, 0.f};
        const uint32_t ab = sb + OFF_D + (g & 1) * ACTL_PITCH + warp * 256 + t * 4;
        const int kr = warp * 128 + (q4 >> 1) * 8 + (lane & 7);
        const uint32_t wa = sb + OFF_WO + kr * 32 + (((q4 & 1) ^ ((kr >> 2) & 1)) << 4);
#pragma unroll
        for (int ks = 0; ks < 8; ks += 2) {
            uint32_t a[4], a2[4];
            ldsm4t(a, wa + ks * 512);
            ldsm4t(a2, wa + ks * 512 + 512);
            mma16816(c, a, lds32(ab + ks * 32), lds32(ab + ks * 32 + 16));
            mma16816(c2, a2, lds32(ab + ks * 32 + 32), lds32(ab + ks * 32 + 48));
        }
        if (t < 2) stsf2(sb + OFF_RED + (warp * 16 + t * 8 + g) * 8, t ? c[2] + c2[2] : c[0] + c2[0], t ? c[3] + c2[3] : c[1] + c2[1]);
    }
    bar_compute();
    if (tid < 16) {
        float s0 = 0.f, s1 = 0.f;
#pragma unroll
        for (int w = 0; w < 8; w++) { float2 v = ldsf2(sb + OFF_RED + (w * 16 + tid) * 8); s0 += v.x; s1 += v.y; }
        str1(gs->x2 + kq * 512 + cg * 16 + tid, tagw(pack2(s0, s1), tag));
    }
    TLREC(16);
    {
        const unsigned tw0 = (unsigned)clock();
        uint32_t n = 0;
        while (!(ok2(ga, tag) && ok2(sbv, tag) && ok2(cbv, tag) && ok1(gbw, tag)) && ++n < SPIN_LIMIT) {
            ga = ldr2(gs->m2 + 2 * tid); sbv = ldr2(gs->m2 + 512 + 2 * tid); cbv = ldr2(gs->m2 + 1024 + 2 * tid);
            gbw = ldr1(gs->m2 + 1536 + (cta & 63) * 8 + (tid & 7));
        }
        const float k00 = 1.f + bflo(cbv.x), k01 = 1.f + bflo(cbv.y), k10 = 1.f + bfhi(cbv.x), k11 = 1.f + bfhi(cbv.y);
        sts32(sb + OFF_E + 2 * ACT_PITCH + tid * 4, pack2(k00, k01));
        sts32(sb + OFF_E + 3 * ACT_PITCH + tid * 4, pack2(k10, k11));
        sts32(sb + OFF_E + 4 * ACT_PITCH + tid * 4, __byte_perm(sbv.x, sbv.y, 0x5410));
        sts32(sb + OFF_E + 5 * ACT_PITCH + tid * 4, __byte_perm(sbv.x, sbv.y, 0x7632));
        uint2 p[4];
        bool ok;
        n = 0;
        hold(tw0, D_X2);
        do {
#pragma unroll
            for (int j = 0; j < 4; j++) p[j] = ldr2(gs->x2 + j * 512 + 2 * tid);
            ok = ok2(p[0], tag) && ok2(p[1], tag) && ok2(p[2], tag) && ok2(p[3], tag);
        } while (!ok && ++n < SPIN_LIMIT);
        const float a00 = (bflo(p[0].x) + bflo(p[1].x)) + (bflo(p[2].x) + bflo(p[3].x));
        const float a10 = (bfhi(p[0].x) + bfhi(p[1].x)) + (bfhi(p[2].x) + bfhi(p[3].x));
        const float a01 = (bflo(p[0].y) + bflo(p[1].y)) + (bflo(p[2].y) + bflo(p[3].y));
        const float a11 = (bfhi(p[0].y) + bfhi(p[1].y)) + (bfhi(p[2].y) + bfhi(p[3].y));
        const float y00 = bflo(xw0) + bflo(ga.x) * a00, y01 = bfhi(xw0) + bflo(ga.y) * a01;
        const float y10 = bflo(xw1) + bfhi(ga.x) * a10, y11 = bfhi(xw1) + bfhi(ga.y) * a11;
        sts32(sb + OFF_E + tid * 4, pack2(y00 * k00, y01 * k01));
        sts32(sb + OFF_E + ACT_PITCH + tid * 4, pack2(y10 * k10, y11 * k11));
        if ((tid >> 2) == (cta & 63)) stsf2(sb + OFF_SM + 192 + (tid & 3) * 8, ab_ ? y10 : y00, ab_ ? y11 : y01);
        const bool u4 = lane & 16, u2 = lane & 8;
        const float s0 = y00 + y01, s1 = y10 + y11, q0 = y00 * y00 + y01 * y01, q1 = y10 * y10 + y11 * y11;
        const float r0 = (u4 ? q0 : s0) + __shfl_xor_sync(0xffffffffu, u4 ? s0 : q0, 16);
        const float r1 = (u4 ? q1 : s1) + __shfl_xor_sync(0xffffffffu, u4 ? s1 : q1, 16);
        float r = (u2 ? r1 : r0) + __shfl_xor_sync(0xffffffffu, u2 ? r0 : r1, 8);
        r += __shfl_xor_sync(0xffffffffu, r, 4); r += __shfl_xor_sync(0xffffffffu, r, 2); r += __shfl_xor_sync(0xffffffffu, r, 1);
        if (!(lane & 7)) stsf(sb + OFF_SM + warp * 16 + (lane >> 3) * 4, r);
    }
    bar_compute();
    TLREC(17);
    if (cta < NFFN) {
        const int mat = warp >> 2, kq4 = warp & 3;
        mbar_wait(BAR(mat ? B_WU : B_WG));
        {
            float c[4] = {0.f, 0.f, 0.f, 0.f}, c2[4] = {0.f, 0.f, 0.f, 0.f};
            const uint32_t ab = sb + OFF_E + (g < 6 ? g : g - 6) * ACT_PITCH + kq4 * 256 + t * 4;
            const int kr = kq4 * 128 + (q4 >> 1) * 8 + (lane & 7);
            const uint32_t wa = sb + (mat ? OFF_WU : OFF_WG) + kr * 32 + (((q4 & 1) ^ ((kr >> 2) & 1)) << 4);
#pragma unroll
            for (int ks = 0; ks < 8; ks += 2) {
                uint32_t a[4], a2[4];
                ldsm4t(a, wa + ks * 512);
                ldsm4t(a2, wa + ks * 512 + 512);
                mma16816(c, a, lds32(ab + ks * 32), lds32(ab + ks * 32 + 16));
                mma16816(c2, a2, lds32(ab + ks * 32 + 32), lds32(ab + ks * 32 + 48));
            }
            float4 st = make_float4(0.f, 0.f, 0.f, 0.f);
#pragma unroll
            for (int w = 0; w < 8; w++) { const float4 v = ldsf4(sb + OFF_SM + w * 16); st.x += v.x; st.y += v.y; st.z += v.z; st.w += v.w; }
            const float m0 = st.x * (1.f / 512.f), m1 = st.y * (1.f / 512.f);
            const float r0 = rsqrtf(fmaxf(st.z * (1.f / 512.f) - m0 * m0, 0.f) + 1e-5f), r1 = rsqrtf(fmaxf(st.w * (1.f / 512.f) - m1 * m1, 0.f) + 1e-5f);
            const float f0 = t == 0 ? r0 : (t == 1 ? -r0 * m0 : (t == 2 ? 1.f : 0.f));
            const float f1 = t == 0 ? r1 : (t == 1 ? -r1 * m1 : (t == 2 ? 1.f : 0.f));
            const float e0 = (c[0] + c2[0]) * f0, e1 = (c[1] + c2[1]) * f1, e2 = (c[2] + c2[2]) * f0, e3 = (c[3] + c2[3]) * f1;
            const bool w2 = t & 2, w1 = t & 1;
            const float h0 = (w2 ? e2 : e0) + __shfl_xor_sync(0xffffffffu, w2 ? e0 : e2, 2);
            const float h1 = (w2 ? e3 : e1) + __shfl_xor_sync(0xffffffffu, w2 ? e1 : e3, 2);
            const float v = (w1 ? h1 : h0) + __shfl_xor_sync(0xffffffffu, w1 ? h0 : h1, 1);
            stsf(sb + OFF_RED + ((warp * 2 + (t & 1)) * 16 + (t >> 1) * 8 + g) * 4, v);
        }
        bar_compute();
        uint32_t b0, b1;
        {
            float gv[4] = {0.f, 0.f, 0.f, 0.f}, uv[4] = {0.f, 0.f, 0.f, 0.f};
            const uint32_t ra = sb + OFF_RED + ((g & 1) * 16 + 2 * t) * 4;
#pragma unroll
            for (int s = 0; s < 4; s++) {
                const float2 x0 = ldsf2(ra + s * 128), x1 = ldsf2(ra + s * 128 + 32);
                const float2 y0 = ldsf2(ra + 512 + s * 128), y1 = ldsf2(ra + 512 + s * 128 + 32);
                gv[0] += x0.x; gv[1] += x0.y; gv[2] += x1.x; gv[3] += x1.y;
                uv[0] += y0.x; uv[1] += y0.y; uv[2] += y1.x; uv[3] += y1.y;
            }
            b0 = pack2(gelu_tanh(gv[0]) * uv[0], gelu_tanh(gv[1]) * uv[1]);
            b1 = pack2(gelu_tanh(gv[2]) * uv[2], gelu_tanh(gv[3]) * uv[3]);
        }
        mbar_wait(BAR(B_WD));
        const int kr = (q4 >> 1) * 8 + (lane & 7);
#pragma unroll
        for (int mi = 0; mi < 4; mi++) {
            uint32_t a[4];
            ldsm4t(a, sb + OFF_WD + warp * 2048 + kr * 128 + (((2 * mi + (q4 & 1)) ^ (lane & 7)) << 4));
            float c[4] = {0.f, 0.f, 0.f, 0.f};
            mma16816(c, a, b0, b1);
            const float v = (t & 2) ? ((t & 1) ? c[3] : c[2]) : ((t & 1) ? c[1] : c[0]);
            const int cons = (t & 1) * 64 + warp * 8 + mi * 2 + (t >> 1);
            str1(gs->e4 + (cons * NFFN + cta) * 8 + g, tagw(__float_as_uint(v), tag));
        }
    }
    TLREC(18);
    if (warp < 7) {
        const uint32_t* pe = gs->e4 + cta * NFFN * 8 + tid * 4;
        uint4 v;
        uint32_t n = 0;
        hold((unsigned)clock(), D_E4);
        do { v = ldr4(pe); } while (!ok4(v, tag) && ++n < SPIN_LIMIT);
        __syncwarp();
        float f0 = __uint_as_float(v.x), f1 = __uint_as_float(v.y), f2 = __uint_as_float(v.z), f3 = __uint_as_float(v.w);
#pragma unroll
        for (int o = 2; o <= 16; o <<= 1) {
            f0 += __shfl_xor_sync(0xffffffffu, f0, o); f1 += __shfl_xor_sync(0xffffffffu, f1, o);
            f2 += __shfl_xor_sync(0xffffffffu, f2, o); f3 += __shfl_xor_sync(0xffffffffu, f3, o);
        }
        if (lane < 2) { stsf2(sb + OFF_CRED + warp * 32 + lane * 16, f0, f1); stsf2(sb + OFF_CRED + warp * 32 + lane * 16 + 8, f2, f3); }
    }
    bar_compute();
    if (tid < 8) {
        float s = 0.f;
#pragma unroll
        for (int w = 0; w < 7; w++) s += ldsf(sb + OFF_CRED + w * 32 + tid * 4);
        const float gb = ab_ ? bfhi(gbw) : bflo(gbw);
        gout[cta * 8 + tid] = __float2bfloat16(ldsf(sb + OFF_SM + 192 + tid * 4) + gb * s);
        if (cta == 0 && tid == 0) str1(gs->epoch, epoch + 1);
    }
    TLREC(19);
}

typedef CUresult (*EncodeFn)(CUtensorMap*, CUtensorMapDataType, cuuint32_t, void*, const cuuint64_t*, const cuuint64_t*,
                             const cuuint32_t*, const cuuint32_t*, CUtensorMapInterleave, CUtensorMapSwizzle,
                             CUtensorMapL2promotion, CUtensorMapFloatOOBfill);

void enc2d(EncodeFn f, CUtensorMap* m, const void* p, uint64_t cols, uint64_t rows, uint32_t bc, uint32_t br, CUtensorMapSwizzle sw) {
    cuuint64_t dims[2] = {cols, rows};
    cuuint64_t strides[1] = {cols * 2};
    cuuint32_t box[2] = {bc, br}, es[2] = {1, 1};
    f(m, CU_TENSOR_MAP_DATA_TYPE_BFLOAT16, 2, const_cast<void*>(p), dims, strides, box, es, CU_TENSOR_MAP_INTERLEAVE_NONE, sw,
      CU_TENSOR_MAP_L2_PROMOTION_NONE, CU_TENSOR_MAP_FLOAT_OOB_FILL_NONE);
}
void enc3d(EncodeFn f, CUtensorMap* m, const void* p, uint64_t rows, uint32_t br, uint32_t bb) {
    cuuint64_t dims[3] = {64, rows, 8};
    cuuint64_t strides[2] = {1024, 128};
    cuuint32_t box[3] = {64, br, bb}, es[3] = {1, 1, 1};
    f(m, CU_TENSOR_MAP_DATA_TYPE_BFLOAT16, 3, const_cast<void*>(p), dims, strides, box, es, CU_TENSOR_MAP_INTERLEAVE_NONE,
      CU_TENSOR_MAP_SWIZZLE_128B, CU_TENSOR_MAP_L2_PROMOTION_NONE, CU_TENSOR_MAP_FLOAT_OOB_FILL_NONE);
}

}

extern "C" void kernel_launch(void* const* d_in, const int* in_sizes, int n_in, void* d_out, int out_size) {
    (void)in_sizes; (void)n_in; (void)out_size;
    static EncodeFn enc = nullptr;
    static Scratch* scratch = nullptr;
    if (!enc) {
        void* fn = nullptr;
        cudaDriverEntryPointQueryResult qr;
        cudaGetDriverEntryPoint("cuTensorMapEncodeTiled", &fn, cudaEnableDefault, &qr);
        enc = (EncodeFn)fn;
        cudaGetSymbolAddress((void**)&scratch, g_s);
        cudaFuncSetAttribute(fused_kernel, cudaFuncAttributeMaxDynamicSharedMemorySize, SMEM_BYTES);
    }
    Maps m;
    enc2d(enc, &m.wq, d_in[2], 4096, 512, 64, 128, CU_TENSOR_MAP_SWIZZLE_128B);
    enc2d(enc, &m.wuk, d_in[3], 4096, 512, 64, 128, CU_TENSOR_MAP_SWIZZLE_128B);
    enc2d(enc, &m.wuv, d_in[4], 4096, 512, 64, 128, CU_TENSOR_MAP_SWIZZLE_128B);
    enc3d(enc, &m.kv, d_in[1], 16384, 64, 2);
    enc2d(enc, &m.wo, d_in[5], 512, 4096, 16, 256, CU_TENSOR_MAP_SWIZZLE_32B);
    enc2d(enc, &m.wm, d_in[11], 3072, 512, 16, 256, CU_TENSOR_MAP_SWIZZLE_32B);
    enc2d(enc, &m.wg, d_in[7], 1792, 512, 16, 256, CU_TENSOR_MAP_SWIZZLE_32B);
    enc2d(enc, &m.wu, d_in[8], 1792, 512, 16, 256, CU_TENSOR_MAP_SWIZZLE_32B);
    enc3d(enc, &m.wd, d_in[9], 1792, 16, 8);
    fused_kernel<<<NCTA, NTHR, SMEM_BYTES>>>((const __nv_bfloat16*)d_in[0], (const __nv_bfloat16*)d_in[10],
                                             (const __nv_bfloat16*)d_in[11], (__nv_bfloat16*)d_out, scratch, m);
}
```

```cpp
#include <cuda_runtime.h>
#include <cuda_bf16.h>
#include <cuda.h>
#include <stdint.h>

#define D_E0 900
#define D_E1 900
#define D_E2 1500
#define D_X1 900
#define D_X2 1100
#define D_E4 1100
#define BOXK 4
#define NBOX 64
#define MBOX 32
#define STAG 370
#define DSH 185
#define PACE_NUM 1220
#define PACE2_NUM 1280
#define PACE3_NUM 1400
#define KVGAP 600
#define PAUSE 2000

namespace {

constexpr int NCTA = 128;
constexpr int NTHR = 320;
constexpr int NFFN = 112;
#define SPIN_LOG 20
constexpr uint32_t SPIN_LIMIT = 1u << SPIN_LOG;

constexpr int OFF_A = 0;
constexpr int OFF_B = 131072;
constexpr int OFF_C = 163840;
constexpr int OFF_D = 196608;
constexpr int OFF_E = 204800;
constexpr int OFF_M = 221184;
constexpr int OFF_BAR = OFF_M;
constexpr int OFF_SC = OFF_BAR + 256;
constexpr int OFF_ACT = OFF_SC + 2080;
constexpr int OFF_QRED = OFF_ACT + 2080;
constexpr int OFF_CRED = OFF_QRED + 2048;
constexpr int OFF_RED = OFF_CRED + 2048;
constexpr int OFF_SM = OFF_RED + 1024;
constexpr int SMEM_BYTES = OFF_SM + 512;
static_assert(SMEM_BYTES <= 232448, "smem");
constexpr int ACT_PITCH = 1040;
constexpr int ACTL_PITCH = 2064;
constexpr int OFF_WO = OFF_A;
constexpr int OFF_WG = OFF_A + 32768;
constexpr int OFF_WU = OFF_A + 65536;
constexpr int OFF_WD = OFF_A + 98304;
constexpr int OFF_WM2 = OFF_C;

enum { B_WQ = 0, B_WUK, B_KV0, B_KV1, B_KV2, B_KV3, B_WUV, B_WM2, B_WO, B_WG, B_WU, B_WD,
       B_QRED, B_S0, B_S1, B_S2, B_S3, B_FREEB, B_FREEA0, B_FREEA2, B_PEERC, B_SFREE, B_COUNT };

struct __align__(1024) Scratch {
    uint32_t e0[1024];
    uint32_t m2[2048];
    uint32_t x2[4 * 512];
    uint32_t x1[4 * 4096];
    uint32_t e1[2 * 2 * 2 * 32 * 128];
    uint32_t ml[32 * 2 * 64 * 8];
    uint32_t e4[128 * NFFN * 8];
    uint32_t e2[32 * 4 * 64 * 64];
    uint32_t epoch[32];
};
__device__ Scratch g_s;
#define TLREC(i)
#define TLREC1(i)
#define TLRECP(i)

struct Maps { CUtensorMap wq, wuk, wuv, kv, wo, wm, wg, wu, wd; };

__device__ __forceinline__ uint32_t smem_u32(const void* p) { return (uint32_t)__cvta_generic_to_shared(p); }
__device__ __forceinline__ void mbar_init(uint32_t bar, uint32_t cnt) { asm volatile("mbarrier.init.shared::cta.b64 [%0], %1;" ::"r"(bar), "r"(cnt) : "memory"); }
__device__ __forceinline__ void mbar_expect(uint32_t bar, uint32_t bytes) { asm volatile("mbarrier.arrive.expect_tx.shared::cta.b64 _, [%0], %1;" ::"r"(bar), "r"(bytes) : "memory"); }
__device__ __forceinline__ void mbar_arrive(uint32_t bar) { asm volatile("mbarrier.arrive.shared::cta.b64 _, [%0];" ::"r"(bar) : "memory"); }
__device__ __forceinline__ bool mbar_try(uint32_t bar) {
    uint32_t ok;
    asm volatile("{\n.reg .pred p;\nmbarrier.try_wait.parity.shared::cta.b64 p, [%1], 0;\nselp.u32 %0, 1, 0, p;\n}\n" : "=r"(ok) : "r"(bar) : "memory");
    return ok;
}
__device__ __forceinline__ bool mbar_test(uint32_t bar) {
    uint32_t ok;
    asm volatile("{\n.reg .pred p;\nmbarrier.test_wait.parity.shared::cta.b64 p, [%1], 0;\nselp.u32 %0, 1, 0, p;\n}\n" : "=r"(ok) : "r"(bar) : "memory");
    return ok;
}
__device__ __forceinline__ void mbar_wait(uint32_t bar) { uint32_t n = 0; while (!mbar_try(bar) && ++n < SPIN_LIMIT) {} }
__device__ __forceinline__ bool elect_one() {
    uint32_t p;
    asm volatile("{\n.reg .pred P;\nelect.sync _|P, 0xffffffff;\nselp.u32 %0,1,0,P;\n}\n" : "=r"(p));
    return p;
}
__device__ __forceinline__ void tma2d(uint32_t dst, const CUtensorMap* m, int c0, int c1, uint32_t bar) {
    asm volatile("cp.async.bulk.tensor.2d.shared::cluster.global.mbarrier::complete_tx::bytes [%0], [%1, {%3, %4}], [%2];"
                 ::"r"(dst), "l"(m), "r"(bar), "r"(c0), "r"(c1) : "memory");
}
__device__ __forceinline__ void tma2d_mc(uint32_t dst, const CUtensorMap* m, int c0, int c1, uint32_t bar) {
    asm volatile("cp.async.bulk.tensor.2d.shared::cluster.global.mbarrier::complete_tx::bytes.multicast::cluster [%0], [%1, {%3, %4}], [%2], %5;"
                 ::"r"(dst), "l"(m), "r"(bar), "r"(c0), "r"(c1), "h"((uint16_t)3) : "memory");
}
__device__ __forceinline__ void tma3d(uint32_t dst, const CUtensorMap* m, int c0, int c1, int c2, uint32_t bar) {
    asm volatile("cp.async.bulk.tensor.3d.shared::cluster.global.mbarrier::complete_tx::bytes [%0], [%1, {%3, %4, %5}], [%2];"
                 ::"r"(dst), "l"(m), "r"(bar), "r"(c0), "r"(c1), "r"(c2) : "memory");
}
__device__ __forceinline__ void bar_compute() { asm volatile("bar.sync 1, 256;" ::: "memory"); }
__device__ __forceinline__ uint32_t mapa(uint32_t addr, uint32_t rank) { uint32_t r; asm("mapa.shared::cluster.u32 %0, %1, %2;" : "=r"(r) : "r"(addr), "r"(rank)); return r; }
__device__ __forceinline__ void st_async32(uint32_t addr, float v, uint32_t bar) {
    asm volatile("st.async.weak.shared::cluster.mbarrier::complete_tx::bytes.f32 [%0], %1, [%2];" ::"r"(addr), "f"(v), "r"(bar) : "memory");
}
__device__ __forceinline__ void st_async128(uint32_t addr, float a, float b, float c, float d, uint32_t bar) {
    asm volatile("st.async.weak.shared::cluster.mbarrier::complete_tx::bytes.v4.f32 [%0], {%1,%2,%3,%4}, [%5];" ::"r"(addr), "f"(a), "f"(b), "f"(c), "f"(d), "r"(bar) : "memory");
}
__device__ __forceinline__ uint32_t ldr1(const uint32_t* p) { uint32_t v; asm volatile("ld.relaxed.gpu.global.u32 %0, [%1];" : "=r"(v) : "l"(p) : "memory"); return v; }
__device__ __forceinline__ uint2 ldr2(const uint32_t* p) { uint2 v; asm volatile("ld.relaxed.gpu.global.v2.u32 {%0,%1}, [%2];" : "=r"(v.x), "=r"(v.y) : "l"(p) : "memory"); return v; }
__device__ __forceinline__ uint4 ldr4(const uint32_t* p) { uint4 v; asm volatile("ld.relaxed.gpu.global.v4.u32 {%0,%1,%2,%3}, [%4];" : "=r"(v.x), "=r"(v.y), "=r"(v.z), "=r"(v.w) : "l"(p) : "memory"); return v; }
__device__ __forceinline__ void str1(uint32_t* p, uint32_t v) { asm volatile("st.relaxed.gpu.global.u32 [%0], %1;" ::"l"(p), "r"(v) : "memory"); }
__device__ __forceinline__ void str4(uint32_t* p, uint4 v) { asm volatile("st.relaxed.gpu.global.v4.u32 [%0], {%1,%2,%3,%4};" ::"l"(p), "r"(v.x), "r"(v.y), "r"(v.z), "r"(v.w) : "memory"); }
__device__ __forceinline__ void ldsm4(uint32_t (&r)[4], uint32_t a) { asm volatile("ldmatrix.sync.aligned.m8n8.x4.shared.b16 {%0,%1,%2,%3}, [%4];" : "=r"(r[0]), "=r"(r[1]), "=r"(r[2]), "=r"(r[3]) : "r"(a) : "memory"); }
__device__ __forceinline__ void ldsm4t(uint32_t (&r)[4], uint32_t a) { asm volatile("ldmatrix.sync.aligned.m8n8.x4.trans.shared.b16 {%0,%1,%2,%3}, [%4];" : "=r"(r[0]), "=r"(r[1]), "=r"(r[2]), "=r"(r[3]) : "r"(a) : "memory"); }
__device__ __forceinline__ void stsm4t(uint32_t a, uint32_t r0, uint32_t r1, uint32_t r2, uint32_t r3) { asm volatile("stmatrix.sync.aligned.m8n8.x4.trans.shared.b16 [%0], {%1,%2,%3,%4};" ::"r"(a), "r"(r0), "r"(r1), "r"(r2), "r"(r3) : "memory"); }
__device__ __forceinline__ void mma16816(float (&c)[4], const uint32_t (&a)[4], uint32_t b0, uint32_t b1) {
    asm volatile("mma.sync.aligned.m16n8k16.row.col.f32.bf16.bf16.f32 {%0,%1,%2,%3}, {%4,%5,%6,%7}, {%8,%9}, {%0,%1,%2,%3};"
                 : "+f"(c[0]), "+f"(c[1]), "+f"(c[2]), "+f"(c[3]) : "r"(a[0]), "r"(a[1]), "r"(a[2]), "r"(a[3]), "r"(b0), "r"(b1));
}
__device__ __forceinline__ uint32_t lds32(uint32_t a) { uint32_t v; asm volatile("ld.shared.u32 %0, [%1];" : "=r"(v) : "r"(a) : "memory"); return v; }
__device__ __forceinline__ float ldsf(uint32_t a) { float v; asm volatile("ld.shared.f32 %0, [%1];" : "=f"(v) : "r"(a) : "memory"); return v; }
__device__ __forceinline__ float2 ldsf2(uint32_t a) { float2 v; asm volatile("ld.shared.v2.f32 {%0,%1}, [%2];" : "=f"(v.x), "=f"(v.y) : "r"(a) : "memory"); return v; }
__device__ __forceinline__ float4 ldsf4(uint32_t a) { float4 v; asm volatile("ld.shared.v4.f32 {%0,%1,%2,%3}, [%4];" : "=f"(v.x), "=f"(v.y), "=f"(v.z), "=f"(v.w) : "r"(a) : "memory"); return v; }
__device__ __forceinline__ uint4 lds128(uint32_t a) { uint4 v; asm volatile("ld.shared.v4.u32 {%0,%1,%2,%3}, [%4];" : "=r"(v.x), "=r"(v.y), "=r"(v.z), "=r"(v.w) : "r"(a) : "memory"); return v; }
__device__ __forceinline__ void sts32(uint32_t a, uint32_t v) { asm volatile("st.shared.u32 [%0], %1;" ::"r"(a), "r"(v) : "memory"); }
__device__ __forceinline__ void sts16(uint32_t a, uint16_t v) { asm volatile("st.shared.u16 [%0], %1;" ::"r"(a), "h"(v) : "memory"); }
__device__ __forceinline__ void stsf(uint32_t a, float v) { asm volatile("st.shared.f32 [%0], %1;" ::"r"(a), "f"(v) : "memory"); }
__device__ __forceinline__ void stsf2(uint32_t a, float x, float y) { asm volatile("st.shared.v2.f32 [%0], {%1,%2};" ::"r"(a), "f"(x), "f"(y) : "memory"); }
__device__ __forceinline__ void sts64(uint32_t a, uint32_t x, uint32_t y) { asm volatile("st.shared.v2.u32 [%0], {%1,%2};" ::"r"(a), "r"(x), "r"(y) : "memory"); }
__device__ __forceinline__ void sts128(uint32_t a, uint4 v) { asm volatile("st.shared.v4.u32 [%0], {%1,%2,%3,%4};" ::"r"(a), "r"(v.x), "r"(v.y), "r"(v.z), "r"(v.w) : "memory"); }
__device__ __forceinline__ uint32_t pack2(float lo, float hi) { uint32_t r; asm("cvt.rn.bf16x2.f32 %0, %1, %2;" : "=r"(r) : "f"(hi), "f"(lo)); return r; }
__device__ __forceinline__ float bflo(uint32_t w) { return __uint_as_float(w << 16); }
__device__ __forceinline__ float bfhi(uint32_t w) { return __uint_as_float(w & 0xffff0000u); }
__device__ __forceinline__ uint32_t tagw(uint32_t w, uint32_t tag) { return (w & ~1u) | tag; }
__device__ __forceinline__ bool ok1(uint32_t v, uint32_t tag) { return ((v ^ tag) & 1u) == 0; }
__device__ __forceinline__ bool ok2(uint2 v, uint32_t tag) { return (((v.x ^ tag) | (v.y ^ tag)) & 1u) == 0; }
__device__ __forceinline__ bool ok4(uint4 v, uint32_t tag) { return (((v.x ^ tag) | (v.y ^ tag) | (v.z ^ tag) | (v.w ^ tag)) & 1u) == 0; }
__device__ __forceinline__ float ex2(float x) { float y; asm("ex2.approx.ftz.f32 %0, %1;" : "=f"(y) : "f"(x)); return y; }
__device__ __forceinline__ float warp_sum(float v) {
#pragma unroll
    for (int o = 16; o; o >>= 1) v += __shfl_xor_sync(0xffffffffu, v, o);
    return v;
}
__device__ __forceinline__ uint32_t desclo(uint32_t addr) { return ((addr & 0x3FFFF) >> 4) | (1u << 16); }
template <int TA>
__device__ __forceinline__ void wgmma_n32(float (&d)[16], uint32_t da, uint32_t db, int acc) {
    asm volatile("{\n.reg .pred p;\n.reg .b64 da, db;\nsetp.ne.b32 p, %18, 0;\n"
                 "mov.b64 da, {%16, %20};\nmov.b64 db, {%17, %20};\n"
                 "wgmma.mma_async.sync.aligned.m64n32k16.f32.bf16.bf16 "
                 "{%0,%1,%2,%3,%4,%5,%6,%7,%8,%9,%10,%11,%12,%13,%14,%15}, da, db, p, 1, 1, %19, 0;\n}\n"
                 : "+f"(d[0]), "+f"(d[1]), "+f"(d[2]), "+f"(d[3]), "+f"(d[4]), "+f"(d[5]), "+f"(d[6]), "+f"(d[7]),
                   "+f"(d[8]), "+f"(d[9]), "+f"(d[10]), "+f"(d[11]), "+f"(d[12]), "+f"(d[13]), "+f"(d[14]), "+f"(d[15])
                 : "r"(da), "r"(db), "r"(acc), "n"(TA), "n"(0x40000040));
}
__device__ __forceinline__ void wg_fence() { asm volatile("wgmma.fence.sync.aligned;" ::: "memory"); }
__device__ __forceinline__ void wg_commit() { asm volatile("wgmma.commit_group.sync.aligned;" ::: "memory"); }
__device__ __forceinline__ void wg_wait0() { asm volatile("wgmma.wait_group.sync.aligned 0;" ::: "memory"); }
template <int N>
__device__ __forceinline__ void reg_fence(float (&d)[N]) {
#pragma unroll
    for (int i = 0; i < N; i++) asm volatile("" : "+f"(d[i])::"memory");
}
__device__ __forceinline__ void hold(unsigned t0, unsigned d) { while ((unsigned)clock() - t0 < d) {} }
__device__ __forceinline__ float gelu_tanh(float x) {
    float u = 0.7978845608028654f * (x + 0.044715f * x * x * x);
    float e = __expf(2.f * u);
    float th = 1.f - __fdividef(2.f, e + 1.f);
    return 0.5f * x * (1.f + th);
}

__device__ __forceinline__ void gemv_pair(uint32_t sb, uint32_t wbase, uint32_t red_off, uint32_t bar_idx, int warp, int lane, uint32_t rank) {
    const int mt = warp & 3, kh = warp >> 2, q = lane >> 3, g = lane >> 2, t = lane & 3;
    float c[4] = {0.f, 0.f, 0.f, 0.f};
    const uint32_t ab = sb + OFF_ACT + (g & 1) * ACT_PITCH + t * 4 + kh * 256;
    const int kr = kh * 128 + (q >> 1) * 8 + (lane & 7);
    const uint32_t wa = wbase + kr * 128 + (((2 * mt + (q & 1)) ^ (lane & 7)) << 4);
#pragma unroll
    for (int ks = 0; ks < 8; ks++) {
        uint32_t a[4];
        ldsm4t(a, wa + ks * 2048);
        mma16816(c, a, lds32(ab + ks * 32), lds32(ab + ks * 32 + 16));
    }
    const float v = (t & 2) ? ((t & 1) ? c[3] : c[2]) : ((t & 1) ? c[1] : c[0]);
    const uint32_t off = red_off + (((rank * 2 + kh) * 2 + (t & 1)) * 64 + mt * 16 + (t >> 1) * 8 + g) * 4;
    const uint32_t bar = OFF_BAR + bar_idx * 8;
    st_async32(mapa(sb + off, rank), v, mapa(sb + bar, rank));
    st_async32(mapa(sb + off, rank ^ 1), v, mapa(sb + bar, rank ^ 1));
}

__global__ void __cluster_dims__(2, 1, 1) __launch_bounds__(NTHR, 1)
fused_kernel(const __nv_bfloat16* __restrict__ gx, const __nv_bfloat16* __restrict__ gc,
             const __nv_bfloat16* __restrict__ gwmod, __nv_bfloat16* __restrict__ gout, Scratch* __restrict__ gs,
             const __grid_constant__ Maps maps) {
    extern __shared__ __align__(1024) unsigned char smem[];
    const uint32_t sb = smem_u32(smem);
    const int tid = threadIdx.x, lane = tid & 31;
    const int warp = __shfl_sync(0xffffffffu, tid >> 5, 0);
    const int cta = blockIdx.x;
    const uint32_t rank = cta & 1;
    const int hh = cta >> 2, pp = (cta >> 1) & 1;
    const int ab_ = cta >> 6, kb = (cta >> 1) & 31;
    const int kq = cta >> 5, cg = cta & 31;
    auto BAR = [&](int i) { return sb + OFF_BAR + i * 8; };

    if (warp == 8) {
        if (lane < 9) asm volatile("prefetch.tensormap [%0];" ::"l"(reinterpret_cast<const CUtensorMap*>(&maps) + lane) : "memory");
        if (elect_one()) {
#pragma unroll
            for (int i = B_WQ; i <= B_WD; i++) mbar_init(BAR(i), 1);
            mbar_init(BAR(B_QRED), 1);
            mbar_init(BAR(B_S0), 1); mbar_init(BAR(B_S1), 1); mbar_init(BAR(B_S2), 1); mbar_init(BAR(B_S3), 1);
            mbar_init(BAR(B_FREEB), 1); mbar_init(BAR(B_PEERC), 8); mbar_init(BAR(B_SFREE), 8);
            mbar_init(BAR(B_FREEA0), 8); mbar_init(BAR(B_FREEA2), 16);
            asm volatile("fence.mbarrier_init.release.cluster;" ::: "memory");
            mbar_expect(BAR(B_WQ), 32768);
            mbar_expect(BAR(B_QRED), 2048);
            mbar_expect(BAR(B_S0), 8192); mbar_expect(BAR(B_S1), 8192); mbar_expect(BAR(B_S2), 8192); mbar_expect(BAR(B_S3), 8192);
        }
        __syncwarp();
        asm volatile("barrier.cluster.arrive.relaxed.aligned;" ::: "memory");
        if (elect_one()) {
            const unsigned t0 = (unsigned)clock();
            const unsigned slot = ((cta * 37) & 127) * STAG / 128;
            unsigned due = slot;
            unsigned rate = PACE_NUM;
            auto pace = [&](unsigned kib) { while ((int)((unsigned)clock() - t0 - due) < 0) {} due += rate * kib / 16; };
            auto resync = [&]() { const unsigned now = (unsigned)clock() - t0; if ((int)(now - due) > 0) due = now; };
            auto ld128 = [&](uint32_t dst, const CUtensorMap* m, int c0, int r0, int rows, uint32_t bar) {
#pragma unroll 1
                for (int r = 0; r < rows; r += BOXK * 8) { pace(BOXK); tma2d(dst + r * 128, m, c0, r0 + r, bar); }
            };
            auto ld32 = [&](uint32_t dst, const CUtensorMap* m, int c0, int r0, int rows, uint32_t bar) {
#pragma unroll 1
                for (int r = 0; r < rows; r += NBOX) { pace(NBOX / 32); tma2d(dst + r * 32, m, c0, r0 + r, bar); }
            };
            auto kvload = [&](int ch) {
                mbar_expect(BAR(B_KV0 + ch), 32768);
#pragma unroll 1
                for (int r = 0; r < 256; r += BOXK * 8) {
                    pace(BOXK);
                    tma2d(sb + OFF_A + ch * 32768 + r * 128, &maps.kv, (rank * 4 + (r >> 6)) * 64, ab_ * 8192 + kb * 256 + ch * 64 + (r & 63), BAR(B_KV0 + ch));
                }
            };
            ld128(sb + OFF_B, &maps.wq, hh * 128 + pp * 64, rank * 256, 256, BAR(B_WQ));
            mbar_expect(BAR(B_WUK), 32768);
            ld128(sb + OFF_C, &maps.wuk, hh * 128 + pp * 64, rank * 256, 256, BAR(B_WUK));
            kvload(0);
            kvload(1);
            due += DSH - slot;
            kvload(2);
            kvload(3);
            due += slot;
            TLRECP(20);
            rate = PACE2_NUM;
            due += KVGAP;
            auto l_wuv = [&]() {
                mbar_wait(BAR(B_FREEB));
                mbar_expect(BAR(B_WUV), 32768);
                ld128(sb + OFF_B, &maps.wuv, hh * 128, (cta & 3) * 128, 128, BAR(B_WUV));
                ld128(sb + OFF_B + 16384, &maps.wuv, hh * 128 + 64, (cta & 3) * 128, 128, BAR(B_WUV));
            };
            auto ldmc = [&](uint32_t dst, const CUtensorMap* m, int c0, uint32_t bar) {
                mbar_expect(bar, 32768);
#pragma unroll 1
                for (int r = rank * 256; r < rank * 256 + 256; r += MBOX) { pace(MBOX / 16); tma2d_mc(dst + r * 64, m, c0, r, bar); }
            };
            auto l_wg = [&]() { if (cta < NFFN) ldmc(sb + OFF_WG, &maps.wg, (cta >> 1) * 32, BAR(B_WG)); };
            auto l_wu = [&]() { if (cta < NFFN) ldmc(sb + OFF_WU, &maps.wu, (cta >> 1) * 32, BAR(B_WU)); };
            auto l_wm = [&]() { ldmc(sb + OFF_WM2, &maps.wm, 1024 + (cta >> 1) * 32, BAR(B_WM2)); };
            auto l_wo = [&]() {
                mbar_wait(BAR(B_FREEA0));
                resync();
                mbar_expect(BAR(B_WO), 32768);
                ld32(sb + OFF_WO, &maps.wo, cg * 16, kq * 1024, 1024, BAR(B_WO));
            };
            auto l_wd = [&]() {
                if (cta < NFFN) {
                    mbar_expect(BAR(B_WD), 16384);
#pragma unroll 1
                    for (int j = 0; j < 8; j += BOXK / 2) { pace(BOXK); tma3d(sb + OFF_WD + j * 2048, &maps.wd, 0, cta * 16, j, BAR(B_WD)); }
                }
            };
            auto gap = [&]() { TLRECP(22); mbar_wait(BAR(B_FREEA2)); resync(); due += PAUSE; rate = PACE3_NUM; };
            l_wuv(); l_wo(); gap(); l_wm(); l_wg(); l_wu(); l_wd();
            TLRECP(24);
        }
        __syncwarp();
        asm volatile("barrier.cluster.wait.aligned;" ::: "memory");
        return;
    }

    const uint32_t epoch = ldr1(gs->epoch);

    if (warp == 9) {
        asm volatile("barrier.cluster.arrive.relaxed.aligned;" ::: "memory");
        const uint32_t tag = (epoch + 1) & 1;
        asm volatile("bar.sync 2, 288;" ::: "memory");
        asm volatile("barrier.cluster.wait.aligned;" ::: "memory");
        asm volatile("bar.sync 3, 288;" ::: "memory");
        const int q = lane >> 3, g = lane >> 2, t = lane & 3;
        uint32_t bq[16][4];
#pragma unroll
        for (int i = 0; i < 16; i++) ldsm4(bq[i], sb + OFF_SC + (lane & 1) * ACT_PITCH + q * 16 + i * 64);
        float c0[4] = {0.f, 0.f, 0.f, 0.f}, c1[4] = {0.f, 0.f, 0.f, 0.f}, c2[4] = {0.f, 0.f, 0.f, 0.f}, c3[4] = {0.f, 0.f, 0.f, 0.f};
        const int kr = (q >> 1) * 8 + (lane & 7);
        const uint32_t wa = sb + OFF_WM2 + kr * 64 + (((rank * 2 + (q & 1)) ^ ((kr >> 1) & 3)) << 4);
        mbar_wait(BAR(B_WM2));
#pragma unroll
        for (int i = 0; i < 16; i += 2) {
            uint32_t a0[4], a1[4], a2[4], a3[4];
            ldsm4t(a0, wa + i * 2048); ldsm4t(a1, wa + i * 2048 + 1024); ldsm4t(a2, wa + i * 2048 + 2048); ldsm4t(a3, wa + i * 2048 + 3072);
            mma16816(c0, a0, bq[i][0], bq[i][1]); mma16816(c1, a1, bq[i][2], bq[i][3]);
            mma16816(c2, a2, bq[i + 1][0], bq[i + 1][1]); mma16816(c3, a3, bq[i + 1][2], bq[i + 1][3]);
        }
#pragma unroll
        for (int i = 0; i < 4; i++) { c0[i] += c2[i]; c1[i] += c3[i]; }
        if (t < 2) {
            const uint32_t w = t ? pack2(c0[2] + c1[2], c0[3] + c1[3]) : pack2(c0[0] + c1[0], c0[1] + c1[1]);
            str1(gs->m2 + cta * 16 + t * 8 + g, tagw(w, tag));
        }
        return;
    }

    const int q4 = lane >> 3, g = lane >> 2, t = lane & 3;
    {
        const __nv_bfloat16* src = gwmod + (size_t)tid * 3072 + cta * 8;
        asm volatile("cp.async.cg.shared.global [%0], [%1], 16;" ::"r"(sb + OFF_D + tid * 16), "l"(src) : "memory");
        asm volatile("cp.async.cg.shared.global [%0], [%1], 16;" ::"r"(sb + OFF_D + 4096 + tid * 16), "l"(src + 256 * 3072) : "memory");
        asm volatile("cp.async.commit_group;" ::: "memory");
    }
    const uint32_t xw0 = __ldg(reinterpret_cast<const uint32_t*>(gx) + tid);
    const uint32_t xw1 = __ldg(reinterpret_cast<const uint32_t*>(gx) + 256 + tid);
    const float xh0 = __bfloat162float(gx[rank * 256 + tid]), xh1 = __bfloat162float(gx[512 + rank * 256 + tid]);
    {
        const uint32_t cw0 = __ldg(reinterpret_cast<const uint32_t*>(gc) + tid);
        const uint32_t cw1 = __ldg(reinterpret_cast<const uint32_t*>(gc) + 256 + tid);
        auto silu = [](float v) { return __fdividef(v, 1.f + __expf(-v)); };
        sts32(sb + OFF_SC + tid * 4, pack2(silu(bflo(cw0)), silu(bfhi(cw0))));
        sts32(sb + OFF_SC + ACT_PITCH + tid * 4, pack2(silu(bflo(cw1)), silu(bfhi(cw1))));
        float s0 = bflo(xw0) + bfhi(xw0), s1 = bflo(xw1) + bfhi(xw1);
        s0 = warp_sum(s0); s1 = warp_sum(s1);
        if (lane == 0) stsf2(sb + OFF_SM + warp * 8, s0, s1);
        if (tid < 32) { sts32(sb + OFF_SM + 256 + tid * 4, 0x80000000u); sts32(sb + OFF_SM + 384 + tid * 4, 0u); }
    }
    asm volatile("barrier.cluster.arrive.relaxed.aligned;" ::: "memory");
    asm volatile("cp.async.wait_group 0;" ::: "memory");
    asm volatile("bar.sync 2, 288;" ::: "memory");
    const uint32_t tag = (epoch + 1) & 1;
    TLREC(0);
    float mean0 = 0.f, mean1 = 0.f;
    {
#pragma unroll
        for (int w = 0; w < 8; w++) { float2 v = ldsf2(sb + OFF_SM + w * 8); mean0 += v.x; mean1 += v.y; }
        mean0 *= (1.f / 512.f); mean1 *= (1.f / 512.f);
        float c[4] = {0.f, 0.f, 0.f, 0.f};
        const uint32_t aa = sb + OFF_SC + (g & 1) * ACT_PITCH + warp * 128 + t * 4;
#pragma unroll
        for (int j = 0; j < 2; j++) {
            uint32_t b[4];
            ldsm4t(b, sb + OFF_D + (warp * 64 + j * 32 + lane) * 16);
            uint32_t a[4];
            a[0] = lds32(aa + j * 64); a[2] = lds32(aa + j * 64 + 16); a[1] = 0; a[3] = 0;
            mma16816(c, a, b[0], b[1]);
            a[0] = lds32(aa + j * 64 + 32); a[2] = lds32(aa + j * 64 + 48);
            mma16816(c, a, b[2], b[3]);
        }
        if (g < 2) stsf2(sb + OFF_RED + ((warp * 2 + g) * 8 + 2 * t) * 4, c[0], c[1]);
        float d0 = bflo(xw0) - mean0, d1 = bfhi(xw0) - mean0, d2 = bflo(xw1) - mean1, d3 = bfhi(xw1) - mean1;
        float v0 = warp_sum(d0 * d0 + d1 * d1), v1 = warp_sum(d2 * d2 + d3 * d3);
        if (lane == 0) stsf2(sb + OFF_SM + 64 + warp * 8, v0, v1);
    }
    bar_compute();
    if (tid < 8) {
        float s0 = 0.f, s1 = 0.f;
#pragma unroll
        for (int w = 0; w < 8; w++) { s0 += ldsf(sb + OFF_RED + (w * 16 + tid) * 4); s1 += ldsf(sb + OFF_RED + (w * 16 + 8 + tid) * 4); }
        str1(gs->e0 + cta * 8 + tid, tagw(pack2(s0, s1), tag));
    }
    TLREC(1);
    {
        const unsigned tw0 = (unsigned)clock();
        float v0 = 0.f, v1 = 0.f;
#pragma unroll
        for (int w = 0; w < 8; w++) { float2 v = ldsf2(sb + OFF_SM + 64 + w * 8); v0 += v.x; v1 += v.y; }
        const float r0 = rsqrtf(v0 * (1.f / 512.f) + 1e-5f), r1 = rsqrtf(v1 * (1.f / 512.f) + 1e-5f);
        const uint32_t* ps = gs->e0 + rank * 256 + tid;
        uint32_t sa, ca, n = 0;
        hold(tw0, D_E0);
        do { sa = ldr1(ps); ca = ldr1(ps + 512); } while (!(ok1(sa, tag) && ok1(ca, tag)) && ++n < SPIN_LIMIT);
        const float h0 = (xh0 - mean0) * r0 * (1.f + bflo(ca)) + bflo(sa);
        const float h1 = (xh1 - mean1) * r1 * (1.f + bfhi(ca)) + bfhi(sa);
        const uint32_t hw = pack2(h0, h1);
        sts16(sb + OFF_ACT + tid * 2, (uint16_t)(hw & 0xffff));
        sts16(sb + OFF_ACT + ACT_PITCH + tid * 2, (uint16_t)(hw >> 16));
    }
    asm volatile("barrier.cluster.wait.aligned;" ::: "memory");
    bar_compute();
    TLREC(2);
    mbar_wait(BAR(B_WQ));
    TLREC(3);
    gemv_pair(sb, sb + OFF_B, OFF_QRED, B_QRED, warp, lane, rank);
    mbar_wait(BAR(B_QRED));
    if (tid == 0) mbar_arrive(BAR(B_FREEB));
    if (tid < 64) {
        const int b = tid >> 5, k2 = tid & 31;
        float s0 = 0.f, s1 = 0.f;
#pragma unroll
        for (int s = 0; s < 4; s++) { float2 v = ldsf2(sb + OFF_QRED + ((s * 2 + b) * 64 + 2 * k2) * 4); s0 += v.x; s1 += v.y; }
        sts32(sb + OFF_ACT + b * ACT_PITCH + k2 * 4, pack2(s0, s1));
    }
    bar_compute();
    TLREC(4);
    mbar_wait(BAR(B_WUK));
    TLREC(5);
    {
        uint32_t bf[8];
        const uint32_t ab = sb + OFF_ACT + (g & 1) * ACT_PITCH + t * 4;
#pragma unroll
        for (int ks = 0; ks < 4; ks++) { bf[2 * ks] = lds32(ab + ks * 32); bf[2 * ks + 1] = lds32(ab + ks * 32 + 16); }
#pragma unroll
        for (int mi = 0; mi < 2; mi++) {
            const int m = (warp * 2 + mi) * 16 + (q4 & 1) * 8 + (lane & 7);
            float c[4] = {0.f, 0.f, 0.f, 0.f};
#pragma unroll
            for (int ks = 0; ks < 4; ks++) {
                uint32_t a[4];
                ldsm4(a, sb + OFF_C + m * 128 + (((2 * ks + (q4 >> 1)) ^ (lane & 7)) << 4));
                mma16816(c, a, bf[2 * ks], bf[2 * ks + 1]);
            }
            const float v = (t & 2) ? ((t & 1) ? c[3] : c[2]) : ((t & 1) ? c[1] : c[0]);
            const uint32_t w = pack2(v, 0.f);
            sts16(sb + OFF_RED + (t & 1) * 512 + ((warp * 2 + mi) * 16 + (t >> 1) * 8 + g) * 2, (uint16_t)(w & 0xffff));
        }
    }
    __syncwarp();
    if (lane == 0) {
        asm volatile("mbarrier.arrive.relaxed.cluster.shared::cluster.b64 _, [%0];" ::"r"(mapa(BAR(B_PEERC), rank ^ 1)) : "memory");
    }
    if (lane < 8) {
        const int b = lane >> 2;
        uint4 v = lds128(sb + OFF_RED + b * 512 + warp * 64 + (lane & 3) * 16);
        v.x = tagw(v.x, tag); v.y = tagw(v.y, tag); v.z = tagw(v.z, tag); v.w = tagw(v.w, tag);
        str4(gs->e1 + (((b * 2 + rank) * 2 + pp) * 32 + hh) * 128 + warp * 16 + (lane & 3) * 4, v);
    }
    TLREC(6);
    {
        const uint32_t* base = gs->e1 + ((ab_ * 2 + rank) * 2) * 32 * 128 + warp * 4 * 128;
        hold((unsigned)clock(), D_E1);
        {
            const uint32_t* pr = base + ((lane >> 2) & 1) * 32 * 128 + (lane >> 3) * 128 + (lane & 3) * 32 + 28;
            uint32_t n = 0;
            bool ok;
            do { ok = ok4(ldr4(pr), tag); } while (!__all_sync(0xffffffffu, ok) && ++n < SPIN_LIMIT);
        }
        uint4 v[8];
        uint32_t n = 0;
        bool ok;
        do {
#pragma unroll
            for (int j = 0; j < 8; j++) v[j] = ldr4(base + (j & 1) * 32 * 128 + (j >> 1) * 128 + lane * 4);
            ok = true;
#pragma unroll
            for (int j = 0; j < 8; j++) ok = ok && ok4(v[j], tag);
        } while (!ok && ++n < SPIN_LIMIT);
#pragma unroll
        for (int j = 0; j < 4; j++) {
            const uint4 a = v[2 * j], b = v[2 * j + 1];
            uint4 o;
            o.x = pack2(bflo(a.x) + bflo(b.x), bfhi(a.x) + bfhi(b.x));
            o.y = pack2(bflo(a.y) + bflo(b.y), bfhi(a.y) + bfhi(b.y));
            o.z = pack2(bflo(a.z) + bflo(b.z), bfhi(a.z) + bfhi(b.z));
            o.w = pack2(bflo(a.w) + bflo(b.w), bfhi(a.w) + bfhi(b.w));
            const int head = warp * 4 + j;
            sts128(sb + OFF_E + (lane >> 3) * 4096 + head * 128 + (((lane & 7) ^ (head & 7)) << 4), o);
        }
    }
    asm volatile("fence.proxy.async.shared::cta;" ::: "memory");
    mbar_wait(BAR(B_PEERC));
    asm volatile("bar.sync 3, 288;" ::: "memory");
    TLREC(7);
    const int wg = warp >> 2, wi = warp & 3, tw = tid & 127;
    {
        constexpr float SC = 0.08838834764831845f * 1.4426950408889634f;
        float o0[16], o1[16], lsum[8], mold[8];
        const uint32_t dA = desclo(sb + OFF_A), dD = desclo(sb + OFF_D), dE = desclo(sb + OFF_E);
#pragma unroll
        for (int i = 0; i < 8; i++) { lsum[i] = 0.f; mold[i] = 0.f; }
#pragma unroll
        for (int i = 0; i < 16; i++) { o0[i] = 0.f; o1[i] = 0.f; }
#pragma unroll 1
        for (int s = 0; s < 2; s++) {
            const int ch = 2 * s + wg;
            float sacc[16];
            mbar_wait(BAR(B_KV0 + ch));
            TLREC1(8 + (s == 0) * 2);
            wg_fence();
#pragma unroll
            for (int cb = 0; cb < 4; cb++)
#pragma unroll
                for (int ks = 0; ks < 4; ks++)
                    wgmma_n32<0>(sacc, dA + ch * 2048 + cb * 512 + ks * 2, dE + cb * 256 + ks * 2, (cb | ks) != 0);
            wg_commit();
            if (s) mbar_wait(BAR(B_SFREE));
            wg_wait0();
            reg_fence(sacc);
            TLREC1(26);
            {
                const uint32_t so = OFF_C + wg * 8192 + tw * 16;
                const uint32_t ra = mapa(sb + so, rank ^ 1), rb = mapa(BAR(B_S0 + ch), rank ^ 1);
#pragma unroll
                for (int j = 0; j < 4; j++) st_async128(ra + j * 2048, sacc[4 * j], sacc[4 * j + 1], sacc[4 * j + 2], sacc[4 * j + 3], rb);
                mbar_wait(BAR(B_S0 + ch));
#pragma unroll
                for (int j = 0; j < 4; j++) {
                    const float4 p = ldsf4(sb + so + j * 2048);
                    sacc[4 * j] = (sacc[4 * j] + p.x) * SC; sacc[4 * j + 1] = (sacc[4 * j + 1] + p.y) * SC;
                    sacc[4 * j + 2] = (sacc[4 * j + 2] + p.z) * SC; sacc[4 * j + 3] = (sacc[4 * j + 3] + p.w) * SC;
                }
                TLREC1(27);
                float mx[8];
#pragma unroll
                for (int j = 0; j < 4; j++) { mx[2 * j] = fmaxf(sacc[4 * j], sacc[4 * j + 2]); mx[2 * j + 1] = fmaxf(sacc[4 * j + 1], sacc[4 * j + 3]); }
                const bool u4 = lane & 16, u2 = lane & 8, u1 = lane & 4;
                float y[4], z[2];
#pragma unroll
                for (int i = 0; i < 4; i++) { const float keep = u4 ? mx[i + 4] : mx[i], send = u4 ? mx[i] : mx[i + 4]; y[i] = fmaxf(keep, __shfl_xor_sync(0xffffffffu, send, 16)); }
#pragma unroll
                for (int i = 0; i < 2; i++) { const float keep = u2 ? y[i + 2] : y[i], send = u2 ? y[i] : y[i + 2]; z[i] = fmaxf(keep, __shfl_xor_sync(0xffffffffu, send, 8)); }
                const float keep = u1 ? z[1] : z[0], send = u1 ? z[0] : z[1];
                const float r = fmaxf(keep, __shfl_xor_sync(0xffffffffu, send, 4));
                int key = __float_as_int(r);
                key = key >= 0 ? key : key ^ 0x7fffffff;
                const int head = 8 * (g >> 1) + 2 * t + (g & 1);
                asm volatile("red.shared.max.s32 [%0], %1;" ::"r"(sb + OFF_SM + 256 + head * 4), "r"(key) : "memory");
                if (s == 0 && lane == 0)
                    asm volatile("mbarrier.arrive.relaxed.cluster.shared::cluster.b64 _, [%0];" ::"r"(mapa(BAR(B_SFREE), rank ^ 1)) : "memory");
            }
            bar_compute();
            TLREC1(28);
            float mnew[8], alpha[8];
#pragma unroll
            for (int j = 0; j < 4; j++) {
                const float2 kk = ldsf2(sb + OFF_SM + 256 + (8 * j + 2 * t) * 4);
                int k0 = __float_as_int(kk.x), k1 = __float_as_int(kk.y);
                k0 = k0 >= 0 ? k0 : k0 ^ 0x7fffffff; k1 = k1 >= 0 ? k1 : k1 ^ 0x7fffffff;
                mnew[2 * j] = __int_as_float(k0); mnew[2 * j + 1] = __int_as_float(k1);
            }
            {
                uint32_t pk[8];
#pragma unroll
                for (int j = 0; j < 4; j++) {
                    const float p0 = ex2(sacc[4 * j] - mnew[2 * j]), p1 = ex2(sacc[4 * j + 1] - mnew[2 * j + 1]);
                    const float p2 = ex2(sacc[4 * j + 2] - mnew[2 * j]), p3 = ex2(sacc[4 * j + 3] - mnew[2 * j + 1]);
                    pk[2 * j] = pack2(p0, p1); pk[2 * j + 1] = pack2(p2, p3);
                }
                const int hrow = (q4 >> 1) * 8 + (lane & 7);
                const uint32_t pa = sb + OFF_D + wg * 4096 + hrow * 128 + (((2 * wi + (q4 & 1)) ^ (lane & 7)) << 4);
                stsm4t(pa, pk[0], pk[1], pk[2], pk[3]);
                stsm4t(pa + 2048, pk[4], pk[5], pk[6], pk[7]);
                asm volatile("fence.proxy.async.shared::cta;" ::: "memory");
#pragma unroll
                for (int j = 0; j < 4; j++) {
                    sacc[2 * j] = bflo(pk[2 * j]) + bflo(pk[2 * j + 1]);
                    sacc[2 * j + 1] = bfhi(pk[2 * j]) + bfhi(pk[2 * j + 1]);
                }
            }
            if (s) {
#pragma unroll
                for (int i = 0; i < 8; i++) { alpha[i] = ex2(mold[i] - mnew[i]); lsum[i] = lsum[i] * alpha[i] + sacc[i]; }
#pragma unroll
                for (int j = 0; j < 4; j++) {
                    o0[4 * j] *= alpha[2 * j]; o0[4 * j + 1] *= alpha[2 * j + 1]; o0[4 * j + 2] *= alpha[2 * j]; o0[4 * j + 3] *= alpha[2 * j + 1];
                    o1[4 * j] *= alpha[2 * j]; o1[4 * j + 1] *= alpha[2 * j + 1]; o1[4 * j + 2] *= alpha[2 * j]; o1[4 * j + 3] *= alpha[2 * j + 1];
                }
            } else {
#pragma unroll
                for (int i = 0; i < 8; i++) { mold[i] = mnew[i]; lsum[i] = sacc[i]; }
            }
            mbar_wait(BAR(B_KV0 + (ch ^ 1)));
            bar_compute();
            TLREC1(29);
            wg_fence();
#pragma unroll
            for (int ks = 0; ks < 8; ks++) {
                const uint32_t ka = dA + (s * 2 + (ks >> 2)) * 2048 + wg * 1024 + (ks & 3) * 128;
                const uint32_t db = dD + (ks >> 2) * 256 + (ks & 3) * 2;
                wgmma_n32<1>(o0, ka, db, 1);
                wgmma_n32<1>(o1, ka + 512, db, 1);
            }
            wg_commit();
            if (s == 1) {
                const bool u4 = lane & 16, u2 = lane & 8, u1 = lane & 4;
                float y[4], z[2];
#pragma unroll
                for (int i = 0; i < 4; i++) { const float keep = u4 ? lsum[i + 4] : lsum[i], send = u4 ? lsum[i] : lsum[i + 4]; y[i] = keep + __shfl_xor_sync(0xffffffffu, send, 16); }
#pragma unroll
                for (int i = 0; i < 2; i++) { const float keep = u2 ? y[i + 2] : y[i], send = u2 ? y[i] : y[i + 2]; z[i] = keep + __shfl_xor_sync(0xffffffffu, send, 8); }
                const float keep = u1 ? z[1] : z[0], send = u1 ? z[0] : z[1];
                const float r = keep + __shfl_xor_sync(0xffffffffu, send, 4);
                const int head = 8 * (g >> 1) + 2 * t + (g & 1);
                asm volatile("red.shared.add.f32 [%0], %1;" ::"r"(sb + OFF_SM + 384 + head * 4), "f"(r) : "memory");
            }
            wg_wait0();
            reg_fence(o0); reg_fence(o1);
            if (lane == 0) {
                mbar_arrive(BAR(s ? B_FREEA2 : B_FREEA0));
                if (s) asm volatile("mbarrier.arrive.relaxed.cluster.shared::cluster.b64 _, [%0];" ::"r"(mapa(BAR(B_FREEA2), rank ^ 1)) : "memory");
            }
            TLREC1(9 + (s == 0) * 21);
        }
        TLREC(31);
        {
            const int hrow = (q4 >> 1) * 8 + (lane & 7);
#pragma unroll
            for (int mi = 0; mi < 2; mi++) {
                const float(&o)[16] = mi ? o1 : o0;
                const int chunk = (wg * 2 + mi) * 8 + wi * 2 + (q4 & 1);
                const uint32_t a = sb + OFF_E + hrow * 512 + ((chunk ^ (lane & 7)) << 4);
                stsm4t(a, pack2(o[0], o[1]), pack2(o[2], o[3]), pack2(o[4], o[5]), pack2(o[6], o[7]));
                stsm4t(a + 16 * 512, pack2(o[8], o[9]), pack2(o[10], o[11]), pack2(o[12], o[13]), pack2(o[14], o[15]));
            }
        }
    }
    bar_compute();
    TLREC(11);
    {
        const int part = ab_ * 32 + kb;
#pragma unroll
        for (int j = 0; j < 4; j++) {
            const int head = warp * 4 + j;
            uint4 v = lds128(sb + OFF_E + head * 512 + ((lane ^ (head & 7)) << 4));
            v.x = tagw(v.x, tag); v.y = tagw(v.y, tag); v.z = tagw(v.z, tag); v.w = tagw(v.w, tag);
            str4(gs->e2 + ((head * 4 + rank * 2 + (lane >> 4)) * 64 + part) * 64 + (lane & 15) * 4, v);
        }
        TLREC(21);
        if (lane < 8) {
            const int head = warp * 4 + (lane >> 1);
            int k = (int)lds32(sb + OFF_SM + 256 + head * 4);
            k = k >= 0 ? k : k ^ 0x7fffffff;
            const uint32_t m = tagw((uint32_t)k, tag), l = tagw(lds32(sb + OFF_SM + 384 + head * 4), tag);
            str4(gs->ml + ((head * 2 + rank) * 64 + part) * 8 + (lane & 1) * 4, make_uint4(m, l, m, l));
        }
    }
    TLREC(12);
    uint32_t wf[8][4];
    {
        const unsigned tw0 = (unsigned)clock();
        const int b = warp >> 2, ph = warp & 1;
        const uint32_t* pml = gs->ml + ((hh * 2 + pp) * 64 + b * 32 + lane) * 8;
        const uint32_t* pd = gs->e2 + ((hh * 4 + (cta & 3)) * 64 + b * 32 + ph * 16 + q4) * 64 + (warp & 2) * 16 + (lane & 7) * 4;
        uint2 ml = make_uint2(~tag, ~tag);
        uint4 v[4];
#pragma unroll
        for (int j = 0; j < 4; j++) v[j] = make_uint4(~tag, ~tag, ~tag, ~tag);
        mbar_wait(BAR(B_WUV));
        {
            const int kr = (q4 >> 1) * 8 + (lane & 7);
            const uint32_t wa = sb + OFF_B + (warp >> 2) * 16384 + kr * 128 + (((2 * (warp & 3) + (q4 & 1)) ^ (lane & 7)) << 4);
#pragma unroll
            for (int ks = 0; ks < 8; ks++) ldsm4t(wf[ks], wa + ks * 2048);
        }
        hold(tw0, D_E2);
        uint32_t n = 0;
        bool ok;
        do {
            if (!ok2(ml, tag)) ml = ldr2(pml);
#pragma unroll
            for (int j = 0; j < 4; j++) if (!ok4(v[j], tag)) v[j] = ldr4(pd + j * 4 * 64);
            ok = ok2(ml, tag) && ok4(v[0], tag) && ok4(v[1], tag) && ok4(v[2], tag) && ok4(v[3], tag);
        } while (!ok && ++n < SPIN_LIMIT);
        __syncwarp();
        const float m = __uint_as_float(ml.x);
        float M = m;
#pragma unroll
        for (int o = 16; o; o >>= 1) M = fmaxf(M, __shfl_xor_sync(0xffffffffu, M, o));
        float w = ex2(m - M);
        const float L = warp_sum(w * __uint_as_float(ml.y));
        float a[8];
#pragma unroll
        for (int i = 0; i < 8; i++) a[i] = 0.f;
#pragma unroll
        for (int j = 0; j < 4; j++) {
            const float wj = __shfl_sync(0xffffffffu, w, ph * 16 + j * 4 + q4);
            a[0] += wj * bflo(v[j].x); a[1] += wj * bfhi(v[j].x); a[2] += wj * bflo(v[j].y); a[3] += wj * bfhi(v[j].y);
            a[4] += wj * bflo(v[j].z); a[5] += wj * bfhi(v[j].z); a[6] += wj * bflo(v[j].w); a[7] += wj * bfhi(v[j].w);
        }
        const bool u4 = lane & 16, u2 = lane & 8;
        float y[4], z[2];
#pragma unroll
        for (int i = 0; i < 4; i++) { const float keep = u4 ? a[i + 4] : a[i], send = u4 ? a[i] : a[i + 4]; y[i] = keep + __shfl_xor_sync(0xffffffffu, send, 16); }
#pragma unroll
        for (int i = 0; i < 2; i++) { const float keep = u2 ? y[i + 2] : y[i], send = u2 ? y[i] : y[i + 2]; z[i] = keep + __shfl_xor_sync(0xffffffffu, send, 8); }
        const float rl = __fdividef(1.f, L);
        sts32(sb + OFF_ACT + (ph * 2 + b) * 272 + ((warp & 2) * 32 + (lane & 7) * 8 + q4 * 2) * 2, pack2(z[0] * rl, z[1] * rl));
    }
    bar_compute();
    TLREC(13);
    {
        float c[4] = {0.f, 0.f, 0.f, 0.f}, c2[4] = {0.f, 0.f, 0.f, 0.f};
        const uint32_t ab = sb + OFF_ACT + (lane & 3) * 272 + q4 * 16;
#pragma unroll
        for (int ks = 0; ks < 8; ks += 2) {
            uint32_t bq[4];
            ldsm4(bq, ab + ks * 32);
            mma16816(c, wf[ks], bq[0], bq[1]);
            mma16816(c2, wf[ks + 1], bq[2], bq[3]);
        }
        float x = (t & 2) ? c[2] + c2[2] : c[0] + c2[0], y = (t & 2) ? c[3] + c2[3] : c[1] + c2[1];
        x += __shfl_xor_sync(0xffffffffu, x, 1); y += __shfl_xor_sync(0xffffffffu, y, 1);
        if (!(t & 1)) str1(gs->x1 + (cta & 3) * 4096 + hh * 128 + warp * 16 + (t >> 1) * 8 + g, tagw(pack2(x, y), tag));
    }
    TLREC(14);
    {
        const unsigned tw0 = (unsigned)clock();
        const uint32_t* px = gs->x1 + kq * 1024 + tid * 4;
        mbar_wait(BAR(B_WO));
        {
            const int kr = warp * 128 + (q4 >> 1) * 8 + (lane & 7);
            const uint32_t wa = sb + OFF_WO + kr * 32 + (((q4 & 1) ^ ((kr >> 2) & 1)) << 4);
#pragma unroll
            for (int ks = 0; ks < 8; ks++) ldsm4t(wf[ks], wa + ks * 512);
        }
        uint4 u[4];
        uint32_t n = 0;
        bool ok;
        hold(tw0, D_X1);
        do {
#pragma unroll
            for (int j = 0; j < 4; j++) u[j] = ldr4(px + j * 4096);
            ok = ok4(u[0], tag) && ok4(u[1], tag) && ok4(u[2], tag) && ok4(u[3], tag);
        } while (!ok && ++n < SPIN_LIMIT);
        const uint32_t da = sb + OFF_D + tid * 8;
        sts64(da, pack2((bflo(u[0].x) + bflo(u[1].x)) + (bflo(u[2].x) + bflo(u[3].x)), (bflo(u[0].y) + bflo(u[1].y)) + (bflo(u[2].y) + bflo(u[3].y))),
              pack2((bflo(u[0].z) + bflo(u[1].z)) + (bflo(u[2].z) + bflo(u[3].z)), (bflo(u[0].w) + bflo(u[1].w)) + (bflo(u[2].w) + bflo(u[3].w))));
        sts64(da + ACTL_PITCH, pack2((bfhi(u[0].x) + bfhi(u[1].x)) + (bfhi(u[2].x) + bfhi(u[3].x)), (bfhi(u[0].y) + bfhi(u[1].y)) + (bfhi(u[2].y) + bfhi(u[3].y))),
              pack2((bfhi(u[0].z) + bfhi(u[1].z)) + (bfhi(u[2].z) + bfhi(u[3].z)), (bfhi(u[0].w) + bfhi(u[1].w)) + (bfhi(u[2].w) + bfhi(u[3].w))));
    }
    uint2 ga = ldr2(gs->m2 + 2 * tid), sbv = ldr2(gs->m2 + 512 + 2 * tid), cbv = ldr2(gs->m2 + 1024 + 2 * tid);
    uint32_t gbw = ldr1(gs->m2 + 1536 + (cta & 63) * 8 + (tid & 7));
    __syncwarp();
    TLREC(15);
    {
        float c[4] = {0.f, 0.f, 0.f, 0.f}, c2[4] = {0.f, 0.f, 0.f, 0.f};
        const uint32_t ab = sb + OFF_D + (lane & 1) * ACTL_PITCH + warp * 256 + q4 * 16;
#pragma unroll
        for (int ks = 0; ks < 8; ks += 2) {
            uint32_t bq[4];
            ldsm4(bq, ab + ks * 32);
            mma16816(c, wf[ks], bq[0], bq[1]);
            mma16816(c2, wf[ks + 1], bq[2], bq[3]);
        }
        if (t < 2) stsf2(sb + OFF_RED + (warp * 16 + t * 8 + g) * 8, t ? c[2] + c2[2] : c[0] + c2[0], t ? c[3] + c2[3] : c[1] + c2[1]);
    }
    bar_compute();
    if (tid < 16) {
        float s0 = 0.f, s1 = 0.f;
#pragma unroll
        for (int w = 0; w < 8; w++) { float2 v = ldsf2(sb + OFF_RED + (w * 16 + tid) * 8); s0 += v.x; s1 += v.y; }
        str1(gs->x2 + kq * 512 + cg * 16 + tid, tagw(pack2(s0, s1), tag));
    }
    TLREC(16);
    bool pre;
    const uint32_t wgu = sb + ((warp >> 2) ? OFF_WU : OFF_WG) + ((warp & 3) * 128 + (q4 >> 1) * 8 + (lane & 7)) * 64 + (((rank * 2 + (q4 & 1)) ^ ((lane >> 1) & 3)) << 4);
    {
        const unsigned tw0 = (unsigned)clock();
        uint32_t n = 0;
        while (!(ok2(ga, tag) && ok2(sbv, tag) && ok2(cbv, tag) && ok1(gbw, tag)) && ++n < SPIN_LIMIT) {
            ga = ldr2(gs->m2 + 2 * tid); sbv = ldr2(gs->m2 + 512 + 2 * tid); cbv = ldr2(gs->m2 + 1024 + 2 * tid);
            gbw = ldr1(gs->m2 + 1536 + (cta & 63) * 8 + (tid & 7));
        }
        const float k00 = 1.f + bflo(cbv.x), k01 = 1.f + bflo(cbv.y), k10 = 1.f + bfhi(cbv.x), k11 = 1.f + bfhi(cbv.y);
        sts32(sb + OFF_E + 2 * ACT_PITCH + tid * 4, pack2(k00, k01));
        sts32(sb + OFF_E + 3 * ACT_PITCH + tid * 4, pack2(k10, k11));
        sts32(sb + OFF_E + 4 * ACT_PITCH + tid * 4, __byte_perm(sbv.x, sbv.y, 0x5410));
        sts32(sb + OFF_E + 5 * ACT_PITCH + tid * 4, __byte_perm(sbv.x, sbv.y, 0x7632));
        uint2 p[4];
        bool ok;
        n = 0;
        pre = cta < NFFN && __all_sync(0xffffffffu, mbar_test(BAR((warp >> 2) ? B_WU : B_WG)));
        if (pre) {
#pragma unroll
            for (int ks = 0; ks < 8; ks++) ldsm4t(wf[ks], wgu + ks * 1024);
        }
        hold(tw0, D_X2);
        do {
#pragma unroll
            for (int j = 0; j < 4; j++) p[j] = ldr2(gs->x2 + j * 512 + 2 * tid);
            ok = ok2(p[0], tag) && ok2(p[1], tag) && ok2(p[2], tag) && ok2(p[3], tag);
        } while (!ok && ++n < SPIN_LIMIT);
        const float a00 = (bflo(p[0].x) + bflo(p[1].x)) + (bflo(p[2].x) + bflo(p[3].x));
        const float a10 = (bfhi(p[0].x) + bfhi(p[1].x)) + (bfhi(p[2].x) + bfhi(p[3].x));
        const float a01 = (bflo(p[0].y) + bflo(p[1].y)) + (bflo(p[2].y) + bflo(p[3].y));
        const float a11 = (bfhi(p[0].y) + bfhi(p[1].y)) + (bfhi(p[2].y) + bfhi(p[3].y));
        const float y00 = bflo(xw0) + bflo(ga.x) * a00, y01 = bfhi(xw0) + bflo(ga.y) * a01;
        const float y10 = bflo(xw1) + bfhi(ga.x) * a10, y11 = bfhi(xw1) + bfhi(ga.y) * a11;
        sts32(sb + OFF_E + tid * 4, pack2(y00 * k00, y01 * k01));
        sts32(sb + OFF_E + ACT_PITCH + tid * 4, pack2(y10 * k10, y11 * k11));
        if ((tid >> 2) == (cta & 63)) stsf2(sb + OFF_SM + 192 + (tid & 3) * 8, ab_ ? y10 : y00, ab_ ? y11 : y01);
        const bool u4 = lane & 16, u2 = lane & 8;
        const float s0 = y00 + y01, s1 = y10 + y11, q0 = y00 * y00 + y01 * y01, q1 = y10 * y10 + y11 * y11;
        const float r0 = (u4 ? q0 : s0) + __shfl_xor_sync(0xffffffffu, u4 ? s0 : q0, 16);
        const float r1 = (u4 ? q1 : s1) + __shfl_xor_sync(0xffffffffu, u4 ? s1 : q1, 16);
        float r = (u2 ? r1 : r0) + __shfl_xor_sync(0xffffffffu, u2 ? r0 : r1, 8);
        r += __shfl_xor_sync(0xffffffffu, r, 4); r += __shfl_xor_sync(0xffffffffu, r, 2); r += __shfl_xor_sync(0xffffffffu, r, 1);
        if (!(lane & 7)) stsf(sb + OFF_SM + warp * 16 + (lane >> 3) * 4, r);
    }
    bar_compute();
    TLREC(17);
    if (cta < NFFN) {
        if (!pre) {
            mbar_wait(BAR((warp >> 2) ? B_WU : B_WG));
#pragma unroll
            for (int ks = 0; ks < 8; ks++) ldsm4t(wf[ks], wgu + ks * 1024);
        }
        {
            float c[4] = {0.f, 0.f, 0.f, 0.f}, c2[4] = {0.f, 0.f, 0.f, 0.f};
            const int br = lane & 7;
            const uint32_t ab = sb + OFF_E + (br < 6 ? br : br - 6) * ACT_PITCH + (warp & 3) * 256 + q4 * 16;
#pragma unroll
            for (int ks = 0; ks < 8; ks += 2) {
                uint32_t bq[4];
                ldsm4(bq, ab + ks * 32);
                mma16816(c, wf[ks], bq[0], bq[1]);
                mma16816(c2, wf[ks + 1], bq[2], bq[3]);
            }
            float4 st = make_float4(0.f, 0.f, 0.f, 0.f);
#pragma unroll
            for (int w = 0; w < 8; w++) { const float4 v = ldsf4(sb + OFF_SM + w * 16); st.x += v.x; st.y += v.y; st.z += v.z; st.w += v.w; }
            const float m0 = st.x * (1.f / 512.f), m1 = st.y * (1.f / 512.f);
            const float r0 = rsqrtf(fmaxf(st.z * (1.f / 512.f) - m0 * m0, 0.f) + 1e-5f), r1 = rsqrtf(fmaxf(st.w * (1.f / 512.f) - m1 * m1, 0.f) + 1e-5f);
            const float f0 = t == 0 ? r0 : (t == 1 ? -r0 * m0 : (t == 2 ? 1.f : 0.f));
            const float f1 = t == 0 ? r1 : (t == 1 ? -r1 * m1 : (t == 2 ? 1.f : 0.f));
            const float e0 = (c[0] + c2[0]) * f0, e1 = (c[1] + c2[1]) * f1, e2 = (c[2] + c2[2]) * f0, e3 = (c[3] + c2[3]) * f1;
            const bool w2 = t & 2, w1 = t & 1;
            const float h0 = (w2 ? e2 : e0) + __shfl_xor_sync(0xffffffffu, w2 ? e0 : e2, 2);
            const float h1 = (w2 ? e3 : e1) + __shfl_xor_sync(0xffffffffu, w2 ? e1 : e3, 2);
            const float v = (w1 ? h1 : h0) + __shfl_xor_sync(0xffffffffu, w1 ? h0 : h1, 1);
            stsf(sb + OFF_RED + ((warp * 2 + (t & 1)) * 16 + (t >> 1) * 8 + g) * 4, v);
        }
        mbar_wait(BAR(B_WD));
#pragma unroll
        for (int mi = 0; mi < 4; mi++)
            ldsm4t(wf[mi], sb + OFF_WD + warp * 2048 + ((q4 >> 1) * 8 + (lane & 7)) * 128 + (((2 * mi + (q4 & 1)) ^ (lane & 7)) << 4));
        bar_compute();
        uint32_t b0, b1;
        {
            float gv[4] = {0.f, 0.f, 0.f, 0.f}, uv[4] = {0.f, 0.f, 0.f, 0.f};
            const uint32_t ra = sb + OFF_RED + ((g & 1) * 16 + 2 * t) * 4;
#pragma unroll
            for (int s = 0; s < 4; s++) {
                const float2 x0 = ldsf2(ra + s * 128), x1 = ldsf2(ra + s * 128 + 32);
                const float2 y0 = ldsf2(ra + 512 + s * 128), y1 = ldsf2(ra + 512 + s * 128 + 32);
                gv[0] += x0.x; gv[1] += x0.y; gv[2] += x1.x; gv[3] += x1.y;
                uv[0] += y0.x; uv[1] += y0.y; uv[2] += y1.x; uv[3] += y1.y;
            }
            b0 = pack2(gelu_tanh(gv[0]) * uv[0], gelu_tanh(gv[1]) * uv[1]);
            b1 = pack2(gelu_tanh(gv[2]) * uv[2], gelu_tanh(gv[3]) * uv[3]);
        }
#pragma unroll
        for (int mi = 0; mi < 4; mi++) {
            float c[4] = {0.f, 0.f, 0.f, 0.f};
            mma16816(c, wf[mi], b0, b1);
            const float v = (t & 2) ? ((t & 1) ? c[3] : c[2]) : ((t & 1) ? c[1] : c[0]);
            const int cons = (t & 1) * 64 + warp * 8 + mi * 2 + (t >> 1);
            str1(gs->e4 + (cons * NFFN + cta) * 8 + g, tagw(__float_as_uint(v), tag));
        }
    }
    TLREC(18);
    if (warp < 7) {
        const uint32_t* pe = gs->e4 + cta * NFFN * 8 + tid * 4;
        uint4 v;
        uint32_t n = 0;
        hold((unsigned)clock(), D_E4);
        do { v = ldr4(pe); } while (!ok4(v, tag) && ++n < SPIN_LIMIT);
        __syncwarp();
        float f0 = __uint_as_float(v.x), f1 = __uint_as_float(v.y), f2 = __uint_as_float(v.z), f3 = __uint_as_float(v.w);
#pragma unroll
        for (int o = 2; o <= 16; o <<= 1) {
            f0 += __shfl_xor_sync(0xffffffffu, f0, o); f1 += __shfl_xor_sync(0xffffffffu, f1, o);
            f2 += __shfl_xor_sync(0xffffffffu, f2, o); f3 += __shfl_xor_sync(0xffffffffu, f3, o);
        }
        if (lane < 2) { stsf2(sb + OFF_CRED + warp * 32 + lane * 16, f0, f1); stsf2(sb + OFF_CRED + warp * 32 + lane * 16 + 8, f2, f3); }
    }
    bar_compute();
    if (tid < 8) {
        float s = 0.f;
#pragma unroll
        for (int w = 0; w < 7; w++) s += ldsf(sb + OFF_CRED + w * 32 + tid * 4);
        const float gb = ab_ ? bfhi(gbw) : bflo(gbw);
        gout[cta * 8 + tid] = __float2bfloat16(ldsf(sb + OFF_SM + 192 + tid * 4) + gb * s);
        if (cta == 0 && tid == 0) str1(gs->epoch, epoch + 1);
    }
    TLREC(19);
}

typedef CUresult (*EncodeFn)(CUtensorMap*, CUtensorMapDataType, cuuint32_t, void*, const cuuint64_t*, const cuuint64_t*,
                             const cuuint32_t*, const cuuint32_t*, CUtensorMapInterleave, CUtensorMapSwizzle,
                             CUtensorMapL2promotion, CUtensorMapFloatOOBfill);

void enc2d(EncodeFn f, CUtensorMap* m, const void* p, uint64_t cols, uint64_t rows, uint32_t bc, uint32_t br, CUtensorMapSwizzle sw) {
    cuuint64_t dims[2] = {cols, rows};
    cuuint64_t strides[1] = {cols * 2};
    cuuint32_t box[2] = {bc, br}, es[2] = {1, 1};
    f(m, CU_TENSOR_MAP_DATA_TYPE_BFLOAT16, 2, const_cast<void*>(p), dims, strides, box, es, CU_TENSOR_MAP_INTERLEAVE_NONE, sw,
      CU_TENSOR_MAP_L2_PROMOTION_NONE, CU_TENSOR_MAP_FLOAT_OOB_FILL_NONE);
}
void enc3d(EncodeFn f, CUtensorMap* m, const void* p, uint64_t rows, uint32_t br, uint32_t bb) {
    cuuint64_t dims[3] = {64, rows, 8};
    cuuint64_t strides[2] = {1024, 128};
    cuuint32_t box[3] = {64, br, bb}, es[3] = {1, 1, 1};
    f(m, CU_TENSOR_MAP_DATA_TYPE_BFLOAT16, 3, const_cast<void*>(p), dims, strides, box, es, CU_TENSOR_MAP_INTERLEAVE_NONE,
      CU_TENSOR_MAP_SWIZZLE_128B, CU_TENSOR_MAP_L2_PROMOTION_NONE, CU_TENSOR_MAP_FLOAT_OOB_FILL_NONE);
}

}

extern "C" void kernel_launch(void* const* d_in, const int* in_sizes, int n_in, void* d_out, int out_size) {
    (void)in_sizes; (void)n_in; (void)out_size;
    static EncodeFn enc = nullptr;
    static Scratch* scratch = nullptr;
    if (!enc) {
        void* fn = nullptr;
        cudaDriverEntryPointQueryResult qr;
        cudaGetDriverEntryPoint("cuTensorMapEncodeTiled", &fn, cudaEnableDefault, &qr);
        enc = (EncodeFn)fn;
        cudaGetSymbolAddress((void**)&scratch, g_s);
        cudaFuncSetAttribute(fused_kernel, cudaFuncAttributeMaxDynamicSharedMemorySize, SMEM_BYTES);
    }
    Maps m;
    enc2d(enc, &m.wq, d_in[2], 4096, 512, 64, BOXK * 8, CU_TENSOR_MAP_SWIZZLE_128B);
    enc2d(enc, &m.wuk, d_in[3], 4096, 512, 64, BOXK * 8, CU_TENSOR_MAP_SWIZZLE_128B);
    enc2d(enc, &m.wuv, d_in[4], 4096, 512, 64, BOXK * 8, CU_TENSOR_MAP_SWIZZLE_128B);
    enc2d(enc, &m.kv, d_in[1], 512, 16384, 64, BOXK * 8, CU_TENSOR_MAP_SWIZZLE_128B);
    enc2d(enc, &m.wo, d_in[5], 512, 4096, 16, NBOX, CU_TENSOR_MAP_SWIZZLE_32B);
    enc2d(enc, &m.wm, d_in[11], 3072, 512, 32, MBOX, CU_TENSOR_MAP_SWIZZLE_64B);
    enc2d(enc, &m.wg, d_in[7], 1792, 512, 32, MBOX, CU_TENSOR_MAP_SWIZZLE_64B);
    enc2d(enc, &m.wu, d_in[8], 1792, 512, 32, MBOX, CU_TENSOR_MAP_SWIZZLE_64B);
    enc3d(enc, &m.wd, d_in[9], 1792, 16, BOXK / 2);
    fused_kernel<<<NCTA, NTHR, SMEM_BYTES>>>((const __nv_bfloat16*)d_in[0], (const __nv_bfloat16*)d_in[10],
                                             (const __nv_bfloat16*)d_in[11], (__nv_bfloat16*)d_out, scratch, m);
}
```

```cpp
#include <cuda_runtime.h>
#include <cuda_bf16.h>
#include <cuda.h>
#include <stdint.h>

#define D_E0 900
#define D_E1 1500
#define D_E2 1400
#define D_X1 1000
#define D_X2 1200
#define D_E4 1400
#define BOXK 4
#define NBOX 64
#define MBOX 32
#define STAG 370
#define DSH 185
#define PACE_NUM 1180
#define PACE1_NUM 1050
#define PACE2_NUM 950
#define PACE3_NUM 1400
#define KVGAP 300
#define PAUSE 2200

namespace {

constexpr int NCTA = 128;
constexpr int NTHR = 320;
constexpr int NFFN = 112;
#define SPIN_LOG 20
constexpr uint32_t SPIN_LIMIT = 1u << SPIN_LOG;

constexpr int OFF_A = 0;
constexpr int OFF_B = 131072;
constexpr int OFF_C = 163840;
constexpr int OFF_D = 196608;
constexpr int OFF_E = 204800;
constexpr int OFF_M = 221184;
constexpr int OFF_BAR = OFF_M;
constexpr int OFF_SC = OFF_BAR + 256;
constexpr int OFF_ACT = OFF_SC + 2080;
constexpr int OFF_QRED = OFF_ACT + 2080;
constexpr int OFF_CRED = OFF_QRED + 2048;
constexpr int OFF_RED = OFF_CRED + 2048;
constexpr int OFF_SM = OFF_RED + 1024;
constexpr int SMEM_BYTES = OFF_SM + 512;
static_assert(SMEM_BYTES <= 232448, "smem");
constexpr int ACT_PITCH = 1040;
constexpr int ACTL_PITCH = 2064;
constexpr int OFF_WO = OFF_A;
constexpr int OFF_WG = OFF_A + 32768;
constexpr int OFF_WU = OFF_A + 65536;
constexpr int OFF_WD = OFF_A + 98304;
constexpr int OFF_WM2 = OFF_C;

enum { B_WQ = 0, B_WUK, B_KV0, B_KV1, B_KV2, B_KV3, B_WUV, B_WM2, B_WO, B_WG, B_WU, B_WD,
       B_QRED, B_S0, B_S1, B_S2, B_S3, B_FREEB, B_FREEA0, B_FREEA2, B_PEERC, B_SFREE, B_COUNT };

struct __align__(1024) Scratch {
    uint32_t e0[1024];
    uint32_t m2[2048];
    uint32_t x2[4 * 512];
    uint32_t x1[4 * 4096];
    uint32_t e1[2 * 2 * 2 * 32 * 128];
    uint32_t ml[32 * 2 * 64 * 8];
    uint32_t e4[128 * NFFN * 8];
    uint32_t e2[32 * 4 * 64 * 64];
    uint32_t epoch[32];
};
__device__ Scratch g_s;
#define TLREC(i)
#define TLREC1(i)
#define TLRECP(i)

struct Maps { CUtensorMap wq, wuk, wuv, kv, wo, wm, wg, wu, wd; };

__device__ __forceinline__ uint32_t smem_u32(const void* p) { return (uint32_t)__cvta_generic_to_shared(p); }
__device__ __forceinline__ void mbar_init(uint32_t bar, uint32_t cnt) { asm volatile("mbarrier.init.shared::cta.b64 [%0], %1;" ::"r"(bar), "r"(cnt) : "memory"); }
__device__ __forceinline__ void mbar_expect(uint32_t bar, uint32_t bytes) { asm volatile("mbarrier.arrive.expect_tx.shared::cta.b64 _, [%0], %1;" ::"r"(bar), "r"(bytes) : "memory"); }
__device__ __forceinline__ void mbar_arrive(uint32_t bar) { asm volatile("mbarrier.arrive.shared::cta.b64 _, [%0];" ::"r"(bar) : "memory"); }
__device__ __forceinline__ bool mbar_try(uint32_t bar) {
    uint32_t ok;
    asm volatile("{\n.reg .pred p;\nmbarrier.try_wait.parity.shared::cta.b64 p, [%1], 0;\nselp.u32 %0, 1, 0, p;\n}\n" : "=r"(ok) : "r"(bar) : "memory");
    return ok;
}
__device__ __forceinline__ bool mbar_test(uint32_t bar) {
    uint32_t ok;
    asm volatile("{\n.reg .pred p;\nmbarrier.test_wait.parity.shared::cta.b64 p, [%1], 0;\nselp.u32 %0, 1, 0, p;\n}\n" : "=r"(ok) : "r"(bar) : "memory");
    return ok;
}
__device__ __forceinline__ void mbar_wait(uint32_t bar) { uint32_t n = 0; while (!mbar_try(bar) && ++n < SPIN_LIMIT) {} }
__device__ __forceinline__ bool elect_one() {
    uint32_t p;
    asm volatile("{\n.reg .pred P;\nelect.sync _|P, 0xffffffff;\nselp.u32 %0,1,0,P;\n}\n" : "=r"(p));
    return p;
}
__device__ __forceinline__ void tma2d(uint32_t dst, const CUtensorMap* m, int c0, int c1, uint32_t bar) {
    asm volatile("cp.async.bulk.tensor.2d.shared::cluster.global.mbarrier::complete_tx::bytes [%0], [%1, {%3, %4}], [%2];"
                 ::"r"(dst), "l"(m), "r"(bar), "r"(c0), "r"(c1) : "memory");
}
__device__ __forceinline__ void tma2d_mc(uint32_t dst, const CUtensorMap* m, int c0, int c1, uint32_t bar) {
    asm volatile("cp.async.bulk.tensor.2d.shared::cluster.global.mbarrier::complete_tx::bytes.multicast::cluster [%0], [%1, {%3, %4}], [%2], %5;"
                 ::"r"(dst), "l"(m), "r"(bar), "r"(c0), "r"(c1), "h"((uint16_t)3) : "memory");
}
__device__ __forceinline__ void tma3d(uint32_t dst, const CUtensorMap* m, int c0, int c1, int c2, uint32_t bar) {
    asm volatile("cp.async.bulk.tensor.3d.shared::cluster.global.mbarrier::complete_tx::bytes [%0], [%1, {%3, %4, %5}], [%2];"
                 ::"r"(dst), "l"(m), "r"(bar), "r"(c0), "r"(c1), "r"(c2) : "memory");
}
__device__ __forceinline__ void bar_compute() { asm volatile("bar.sync 1, 256;" ::: "memory"); }
__device__ __forceinline__ uint32_t mapa(uint32_t addr, uint32_t rank) { uint32_t r; asm("mapa.shared::cluster.u32 %0, %1, %2;" : "=r"(r) : "r"(addr), "r"(rank)); return r; }
__device__ __forceinline__ void st_async32(uint32_t addr, float v, uint32_t bar) {
    asm volatile("st.async.weak.shared::cluster.mbarrier::complete_tx::bytes.f32 [%0], %1, [%2];" ::"r"(addr), "f"(v), "r"(bar) : "memory");
}
__device__ __forceinline__ void st_async128(uint32_t addr, float a, float b, float c, float d, uint32_t bar) {
    asm volatile("st.async.weak.shared::cluster.mbarrier::complete_tx::bytes.v4.f32 [%0], {%1,%2,%3,%4}, [%5];" ::"r"(addr), "f"(a), "f"(b), "f"(c), "f"(d), "r"(bar) : "memory");
}
__device__ __forceinline__ uint32_t ldr1(const uint32_t* p) { uint32_t v; asm volatile("ld.relaxed.gpu.global.u32 %0, [%1];" : "=r"(v) : "l"(p) : "memory"); return v; }
__device__ __forceinline__ uint2 ldr2(const uint32_t* p) { uint2 v; asm volatile("ld.relaxed.gpu.global.v2.u32 {%0,%1}, [%2];" : "=r"(v.x), "=r"(v.y) : "l"(p) : "memory"); return v; }
__device__ __forceinline__ uint4 ldr4(const uint32_t* p) { uint4 v; asm volatile("ld.relaxed.gpu.global.v4.u32 {%0,%1,%2,%3}, [%4];" : "=r"(v.x), "=r"(v.y), "=r"(v.z), "=r"(v.w) : "l"(p) : "memory"); return v; }
__device__ __forceinline__ void str1(uint32_t* p, uint32_t v) { asm volatile("st.relaxed.gpu.global.u32 [%0], %1;" ::"l"(p), "r"(v) : "memory"); }
__device__ __forceinline__ void str4(uint32_t* p, uint4 v) { asm volatile("st.relaxed.gpu.global.v4.u32 [%0], {%1,%2,%3,%4};" ::"l"(p), "r"(v.x), "r"(v.y), "r"(v.z), "r"(v.w) : "memory"); }
__device__ __forceinline__ void ldsm4(uint32_t (&r)[4], uint32_t a) { asm volatile("ldmatrix.sync.aligned.m8n8.x4.shared.b16 {%0,%1,%2,%3}, [%4];" : "=r"(r[0]), "=r"(r[1]), "=r"(r[2]), "=r"(r[3]) : "r"(a) : "memory"); }
__device__ __forceinline__ void ldsm4t(uint32_t (&r)[4], uint32_t a) { asm volatile("ldmatrix.sync.aligned.m8n8.x4.trans.shared.b16 {%0,%1,%2,%3}, [%4];" : "=r"(r[0]), "=r"(r[1]), "=r"(r[2]), "=r"(r[3]) : "r"(a) : "memory"); }
__device__ __forceinline__ void stsm4t(uint32_t a, uint32_t r0, uint32_t r1, uint32_t r2, uint32_t r3) { asm volatile("stmatrix.sync.aligned.m8n8.x4.trans.shared.b16 [%0], {%1,%2,%3,%4};" ::"r"(a), "r"(r0), "r"(r1), "r"(r2), "r"(r3) : "memory"); }
__device__ __forceinline__ void mma16816(float (&c)[4], const uint32_t (&a)[4], uint32_t b0, uint32_t b1) {
    asm volatile("mma.sync.aligned.m16n8k16.row.col.f32.bf16.bf16.f32 {%0,%1,%2,%3}, {%4,%5,%6,%7}, {%8,%9}, {%0,%1,%2,%3};"
                 : "+f"(c[0]), "+f"(c[1]), "+f"(c[2]), "+f"(c[3]) : "r"(a[0]), "r"(a[1]), "r"(a[2]), "r"(a[3]), "r"(b0), "r"(b1));
}
__device__ __forceinline__ uint32_t lds32(uint32_t a) { uint32_t v; asm volatile("ld.shared.u32 %0, [%1];" : "=r"(v) : "r"(a) : "memory"); return v; }
__device__ __forceinline__ float ldsf(uint32_t a) { float v; asm volatile("ld.shared.f32 %0, [%1];" : "=f"(v) : "r"(a) : "memory"); return v; }
__device__ __forceinline__ float2 ldsf2(uint32_t a) { float2 v; asm volatile("ld.shared.v2.f32 {%0,%1}, [%2];" : "=f"(v.x), "=f"(v.y) : "r"(a) : "memory"); return v; }
__device__ __forceinline__ float4 ldsf4(uint32_t a) { float4 v; asm volatile("ld.shared.v4.f32 {%0,%1,%2,%3}, [%4];" : "=f"(v.x), "=f"(v.y), "=f"(v.z), "=f"(v.w) : "r"(a) : "memory"); return v; }
__device__ __forceinline__ uint4 lds128(uint32_t a) { uint4 v; asm volatile("ld.shared.v4.u32 {%0,%1,%2,%3}, [%4];" : "=r"(v.x), "=r"(v.y), "=r"(v.z), "=r"(v.w) : "r"(a) : "memory"); return v; }
__device__ __forceinline__ void sts32(uint32_t a, uint32_t v) { asm volatile("st.shared.u32 [%0], %1;" ::"r"(a), "r"(v) : "memory"); }
__device__ __forceinline__ void sts16(uint32_t a, uint16_t v) { asm volatile("st.shared.u16 [%0], %1;" ::"r"(a), "h"(v) : "memory"); }
__device__ __forceinline__ void stsf(uint32_t a, float v) { asm volatile("st.shared.f32 [%0], %1;" ::"r"(a), "f"(v) : "memory"); }
__device__ __forceinline__ void stsf2(uint32_t a, float x, float y) { asm volatile("st.shared.v2.f32 [%0], {%1,%2};" ::"r"(a), "f"(x), "f"(y) : "memory"); }
__device__ __forceinline__ void sts64(uint32_t a, uint32_t x, uint32_t y) { asm volatile("st.shared.v2.u32 [%0], {%1,%2};" ::"r"(a), "r"(x), "r"(y) : "memory"); }
__device__ __forceinline__ void sts128(uint32_t a, uint4 v) { asm volatile("st.shared.v4.u32 [%0], {%1,%2,%3,%4};" ::"r"(a), "r"(v.x), "r"(v.y), "r"(v.z), "r"(v.w) : "memory"); }
__device__ __forceinline__ uint32_t pack2(float lo, float hi) { uint32_t r; asm("cvt.rn.bf16x2.f32 %0, %1, %2;" : "=r"(r) : "f"(hi), "f"(lo)); return r; }
__device__ __forceinline__ float bflo(uint32_t w) { return __uint_as_float(w << 16); }
__device__ __forceinline__ float bfhi(uint32_t w) { return __uint_as_float(w & 0xffff0000u); }
__device__ __forceinline__ uint32_t tagw(uint32_t w, uint32_t tag) { return (w & ~1u) | tag; }
__device__ __forceinline__ bool ok1(uint32_t v, uint32_t tag) { return ((v ^ tag) & 1u) == 0; }
__device__ __forceinline__ bool ok2(uint2 v, uint32_t tag) { return (((v.x ^ tag) | (v.y ^ tag)) & 1u) == 0; }
__device__ __forceinline__ bool ok4(uint4 v, uint32_t tag) { return (((v.x ^ tag) | (v.y ^ tag) | (v.z ^ tag) | (v.w ^ tag)) & 1u) == 0; }
__device__ __forceinline__ float ex2(float x) { float y; asm("ex2.approx.ftz.f32 %0, %1;" : "=f"(y) : "f"(x)); return y; }
__device__ __forceinline__ float warp_sum(float v) {
#pragma unroll
    for (int o = 16; o; o >>= 1) v += __shfl_xor_sync(0xffffffffu, v, o);
    return v;
}
__device__ __forceinline__ uint32_t desclo(uint32_t addr) { return ((addr & 0x3FFFF) >> 4) | (1u << 16); }
template <int TA>
__device__ __forceinline__ void wgmma_n32(float (&d)[16], uint32_t da, uint32_t db, int acc) {
    asm volatile("{\n.reg .pred p;\n.reg .b64 da, db;\nsetp.ne.b32 p, %18, 0;\n"
                 "mov.b64 da, {%16, %20};\nmov.b64 db, {%17, %20};\n"
                 "wgmma.mma_async.sync.aligned.m64n32k16.f32.bf16.bf16 "
                 "{%0,%1,%2,%3,%4,%5,%6,%7,%8,%9,%10,%11,%12,%13,%14,%15}, da, db, p, 1, 1, %19, 0;\n}\n"
                 : "+f"(d[0]), "+f"(d[1]), "+f"(d[2]), "+f"(d[3]), "+f"(d[4]), "+f"(d[5]), "+f"(d[6]), "+f"(d[7]),
                   "+f"(d[8]), "+f"(d[9]), "+f"(d[10]), "+f"(d[11]), "+f"(d[12]), "+f"(d[13]), "+f"(d[14]), "+f"(d[15])
                 : "r"(da), "r"(db), "r"(acc), "n"(TA), "n"(0x40000040));
}
__device__ __forceinline__ void wg_fence() { asm volatile("wgmma.fence.sync.aligned;" ::: "memory"); }
__device__ __forceinline__ void wg_commit() { asm volatile("wgmma.commit_group.sync.aligned;" ::: "memory"); }
__device__ __forceinline__ void wg_wait0() { asm volatile("wgmma.wait_group.sync.aligned 0;" ::: "memory"); }
template <int N>
__device__ __forceinline__ void reg_fence(float (&d)[N]) {
#pragma unroll
    for (int i = 0; i < N; i++) asm volatile("" : "+f"(d[i])::"memory");
}
__device__ __forceinline__ void hold(unsigned t0, unsigned d) { while ((unsigned)clock() - t0 < d) {} }
__device__ __forceinline__ float gelu_tanh(float x) {
    float u = 0.7978845608028654f * (x + 0.044715f * x * x * x);
    float e = __expf(2.f * u);
    float th = 1.f - __fdividef(2.f, e + 1.f);
    return 0.5f * x * (1.f + th);
}

__device__ __forceinline__ void gemv_pair(uint32_t sb, uint32_t wbase, uint32_t red_off, uint32_t bar_idx, int warp, int lane, uint32_t rank) {
    const int mt = warp & 3, kh = warp >> 2, q = lane >> 3, g = lane >> 2, t = lane & 3;
    float c[4] = {0.f, 0.f, 0.f, 0.f};
    const uint32_t ab = sb + OFF_ACT + (g & 1) * ACT_PITCH + t * 4 + kh * 256;
    const int kr = kh * 128 + (q >> 1) * 8 + (lane & 7);
    const uint32_t wa = wbase + kr * 128 + (((2 * mt + (q & 1)) ^ (lane & 7)) << 4);
#pragma unroll
    for (int ks = 0; ks < 8; ks++) {
        uint32_t a[4];
        ldsm4t(a, wa + ks * 2048);
        mma16816(c, a, lds32(ab + ks * 32), lds32(ab + ks * 32 + 16));
    }
    const float v = (t & 2) ? ((t & 1) ? c[3] : c[2]) : ((t & 1) ? c[1] : c[0]);
    const uint32_t off = red_off + (((rank * 2 + kh) * 2 + (t & 1)) * 64 + mt * 16 + (t >> 1) * 8 + g) * 4;
    const uint32_t bar = OFF_BAR + bar_idx * 8;
    st_async32(mapa(sb + off, rank), v, mapa(sb + bar, rank));
    st_async32(mapa(sb + off, rank ^ 1), v, mapa(sb + bar, rank ^ 1));
}

__global__ void __cluster_dims__(2, 1, 1) __launch_bounds__(NTHR, 1)
fused_kernel(const __nv_bfloat16* __restrict__ gx, const __nv_bfloat16* __restrict__ gc,
             const __nv_bfloat16* __restrict__ gwmod, __nv_bfloat16* __restrict__ gout, Scratch* __restrict__ gs,
             const __grid_constant__ Maps maps) {
    extern __shared__ __align__(1024) unsigned char smem[];
    const uint32_t sb = smem_u32(smem);
    const int tid = threadIdx.x, lane = tid & 31;
    const int warp = __shfl_sync(0xffffffffu, tid >> 5, 0);
    const int cta = blockIdx.x;
    const uint32_t rank = cta & 1;
    const int hh = cta >> 2, pp = (cta >> 1) & 1;
    const int ab_ = cta >> 6, kb = (cta >> 1) & 31;
    const int kq = cta >> 5, cg = cta & 31;
    auto BAR = [&](int i) { return sb + OFF_BAR + i * 8; };

    if (warp < 8) {
        const __nv_bfloat16* src = gwmod + (size_t)tid * 3072 + cta * 8;
        asm volatile("cp.async.cg.shared.global [%0], [%1], 16;" ::"r"(sb + OFF_D + tid * 16), "l"(src) : "memory");
        asm volatile("cp.async.cg.shared.global [%0], [%1], 16;" ::"r"(sb + OFF_D + 4096 + tid * 16), "l"(src + 256 * 3072) : "memory");
        asm volatile("cp.async.commit_group;" ::: "memory");
    }

    if (warp == 8) {
        if (lane < 9) asm volatile("prefetch.tensormap [%0];" ::"l"(reinterpret_cast<const CUtensorMap*>(&maps) + lane) : "memory");
        if (elect_one()) {
#pragma unroll
            for (int i = B_WQ; i <= B_WD; i++) mbar_init(BAR(i), 1);
            mbar_init(BAR(B_QRED), 1);
            mbar_init(BAR(B_S0), 1); mbar_init(BAR(B_S1), 1); mbar_init(BAR(B_S2), 1); mbar_init(BAR(B_S3), 1);
            mbar_init(BAR(B_FREEB), 1); mbar_init(BAR(B_PEERC), 8); mbar_init(BAR(B_SFREE), 8);
            mbar_init(BAR(B_FREEA0), 8); mbar_init(BAR(B_FREEA2), 16);
            asm volatile("fence.mbarrier_init.release.cluster;" ::: "memory");
            mbar_expect(BAR(B_WQ), 32768);
            mbar_expect(BAR(B_QRED), 2048);
            mbar_expect(BAR(B_S0), 8192); mbar_expect(BAR(B_S1), 8192); mbar_expect(BAR(B_S2), 8192); mbar_expect(BAR(B_S3), 8192);
        }
        __syncwarp();
        asm volatile("barrier.cluster.arrive.relaxed.aligned;" ::: "memory");
        if (elect_one()) {
            const unsigned t0 = (unsigned)clock();
            const unsigned slot = ((cta * 37) & 127) * STAG / 128;
            unsigned due = slot;
            unsigned rate = PACE1_NUM;
            auto pace = [&](unsigned kib) { while ((int)((unsigned)clock() - t0 - due) < 0) {} due += rate * kib / 16; };
            auto resync = [&]() { const unsigned now = (unsigned)clock() - t0; if ((int)(now - due) > 0) due = now; };
            auto ld128 = [&](uint32_t dst, const CUtensorMap* m, int c0, int r0, int rows, uint32_t bar) {
#pragma unroll 1
                for (int r = 0; r < rows; r += BOXK * 8) { pace(BOXK); tma2d(dst + r * 128, m, c0, r0 + r, bar); }
            };
            auto ld32 = [&](uint32_t dst, const CUtensorMap* m, int c0, int r0, int rows, uint32_t bar) {
#pragma unroll 1
                for (int r = 0; r < rows; r += NBOX) { pace(NBOX / 32); tma2d(dst + r * 32, m, c0, r0 + r, bar); }
            };
            auto kvload = [&](int ch) {
                mbar_expect(BAR(B_KV0 + ch), 32768);
#pragma unroll 1
                for (int r = 0; r < 256; r += BOXK * 8) {
                    pace(BOXK);
                    tma2d(sb + OFF_A + ch * 32768 + r * 128, &maps.kv, (rank * 4 + (r >> 6)) * 64, ab_ * 8192 + kb * 256 + ch * 64 + (r & 63), BAR(B_KV0 + ch));
                }
            };
            ld128(sb + OFF_B, &maps.wq, hh * 128 + pp * 64, rank * 256, 256, BAR(B_WQ));
            mbar_expect(BAR(B_WUK), 32768);
            ld128(sb + OFF_C, &maps.wuk, hh * 128 + pp * 64, rank * 256, 256, BAR(B_WUK));
            rate = PACE_NUM;
            kvload(0);
            kvload(1);
            due += DSH - slot;
            kvload(2);
            kvload(3);
            due += slot;
            TLRECP(20);
            rate = PACE2_NUM;
            due += KVGAP;
            auto l_wuv = [&]() {
                mbar_wait(BAR(B_FREEB));
                mbar_expect(BAR(B_WUV), 32768);
                ld128(sb + OFF_B, &maps.wuv, hh * 128, (cta & 3) * 128, 128, BAR(B_WUV));
                ld128(sb + OFF_B + 16384, &maps.wuv, hh * 128 + 64, (cta & 3) * 128, 128, BAR(B_WUV));
            };
            auto ldmc = [&](uint32_t dst, const CUtensorMap* m, int c0, uint32_t bar) {
                mbar_expect(bar, 32768);
#pragma unroll 1
                for (int r = rank * 256; r < rank * 256 + 256; r += MBOX) { pace(MBOX / 16); tma2d_mc(dst + r * 64, m, c0, r, bar); }
            };
            auto l_wg = [&]() { if (cta < NFFN) ldmc(sb + OFF_WG, &maps.wg, (cta >> 1) * 32, BAR(B_WG)); };
            auto l_wu = [&]() { if (cta < NFFN) ldmc(sb + OFF_WU, &maps.wu, (cta >> 1) * 32, BAR(B_WU)); };
            auto l_wm = [&]() { ldmc(sb + OFF_WM2, &maps.wm, 1024 + (cta >> 1) * 32, BAR(B_WM2)); };
            auto l_wo = [&]() {
                mbar_wait(BAR(B_FREEA0));
                resync();
                mbar_expect(BAR(B_WO), 32768);
                ld32(sb + OFF_WO, &maps.wo, cg * 16, kq * 1024, 1024, BAR(B_WO));
            };
            auto l_wd = [&]() {
                if (cta < NFFN) {
                    mbar_expect(BAR(B_WD), 16384);
#pragma unroll 1
                    for (int j = 0; j < 8; j += BOXK / 2) { pace(BOXK); tma3d(sb + OFF_WD + j * 2048, &maps.wd, 0, cta * 16, j, BAR(B_WD)); }
                }
            };
            auto gap = [&]() { TLRECP(22); mbar_wait(BAR(B_FREEA2)); resync(); due += PAUSE; rate = PACE3_NUM; };
            l_wuv(); l_wo(); gap(); l_wm(); l_wg(); l_wu(); l_wd();
            TLRECP(24);
        }
        __syncwarp();
        asm volatile("barrier.cluster.wait.aligned;" ::: "memory");
        return;
    }

    const uint32_t epoch = ldr1(gs->epoch);

    if (warp == 9) {
        asm volatile("barrier.cluster.arrive.relaxed.aligned;" ::: "memory");
        const uint32_t tag = (epoch + 1) & 1;
        asm volatile("bar.sync 2, 288;" ::: "memory");
        asm volatile("barrier.cluster.wait.aligned;" ::: "memory");
        asm volatile("bar.sync 3, 288;" ::: "memory");
        const int q = lane >> 3, g = lane >> 2, t = lane & 3;
        uint32_t bq[16][4];
#pragma unroll
        for (int i = 0; i < 16; i++) ldsm4(bq[i], sb + OFF_SC + (lane & 1) * ACT_PITCH + q * 16 + i * 64);
        float c0[4] = {0.f, 0.f, 0.f, 0.f}, c1[4] = {0.f, 0.f, 0.f, 0.f}, c2[4] = {0.f, 0.f, 0.f, 0.f}, c3[4] = {0.f, 0.f, 0.f, 0.f};
        const int kr = (q >> 1) * 8 + (lane & 7);
        const uint32_t wa = sb + OFF_WM2 + kr * 64 + (((rank * 2 + (q & 1)) ^ ((kr >> 1) & 3)) << 4);
        mbar_wait(BAR(B_WM2));
#pragma unroll
        for (int i = 0; i < 16; i += 2) {
            uint32_t a0[4], a1[4], a2[4], a3[4];
            ldsm4t(a0, wa + i * 2048); ldsm4t(a1, wa + i * 2048 + 1024); ldsm4t(a2, wa + i * 2048 + 2048); ldsm4t(a3, wa + i * 2048 + 3072);
            mma16816(c0, a0, bq[i][0], bq[i][1]); mma16816(c1, a1, bq[i][2], bq[i][3]);
            mma16816(c2, a2, bq[i + 1][0], bq[i + 1][1]); mma16816(c3, a3, bq[i + 1][2], bq[i + 1][3]);
        }
#pragma unroll
        for (int i = 0; i < 4; i++) { c0[i] += c2[i]; c1[i] += c3[i]; }
        if (t < 2) {
            const uint32_t w = t ? pack2(c0[2] + c1[2], c0[3] + c1[3]) : pack2(c0[0] + c1[0], c0[1] + c1[1]);
            str1(gs->m2 + cta * 16 + t * 8 + g, tagw(w, tag));
        }
        return;
    }

    const int q4 = lane >> 3, g = lane >> 2, t = lane & 3;
    const uint32_t cw0 = ldr1(reinterpret_cast<const uint32_t*>(gc) + tid);
    const uint32_t cw1 = ldr1(reinterpret_cast<const uint32_t*>(gc) + 256 + tid);
    const uint32_t xw0 = ldr1(reinterpret_cast<const uint32_t*>(gx) + tid);
    const uint32_t xw1 = ldr1(reinterpret_cast<const uint32_t*>(gx) + 256 + tid);
    const float xh0 = __bfloat162float(gx[rank * 256 + tid]), xh1 = __bfloat162float(gx[512 + rank * 256 + tid]);
    {
        auto silu = [](float v) { return __fdividef(v, 1.f + __expf(-v)); };
        sts32(sb + OFF_SC + tid * 4, pack2(silu(bflo(cw0)), silu(bfhi(cw0))));
        sts32(sb + OFF_SC + ACT_PITCH + tid * 4, pack2(silu(bflo(cw1)), silu(bfhi(cw1))));
        float s0 = bflo(xw0) + bfhi(xw0), s1 = bflo(xw1) + bfhi(xw1);
        s0 = warp_sum(s0); s1 = warp_sum(s1);
        if (lane == 0) stsf2(sb + OFF_SM + warp * 8, s0, s1);
        if (tid < 32) { sts32(sb + OFF_SM + 256 + tid * 4, 0x80000000u); sts32(sb + OFF_SM + 384 + tid * 4, 0u); }
    }
    asm volatile("barrier.cluster.arrive.relaxed.aligned;" ::: "memory");
    asm volatile("cp.async.wait_group 0;" ::: "memory");
    asm volatile("bar.sync 2, 288;" ::: "memory");
    const uint32_t tag = (epoch + 1) & 1;
    TLREC(0);
    float mean0 = 0.f, mean1 = 0.f;
    {
#pragma unroll
        for (int w = 0; w < 8; w++) { float2 v = ldsf2(sb + OFF_SM + w * 8); mean0 += v.x; mean1 += v.y; }
        mean0 *= (1.f / 512.f); mean1 *= (1.f / 512.f);
        float c[4] = {0.f, 0.f, 0.f, 0.f};
        const uint32_t aa = sb + OFF_SC + (g & 1) * ACT_PITCH + warp * 128 + t * 4;
#pragma unroll
        for (int j = 0; j < 2; j++) {
            uint32_t b[4];
            ldsm4t(b, sb + OFF_D + (warp * 64 + j * 32 + lane) * 16);
            uint32_t a[4];
            a[0] = lds32(aa + j * 64); a[2] = lds32(aa + j * 64 + 16); a[1] = 0; a[3] = 0;
            mma16816(c, a, b[0], b[1]);
            a[0] = lds32(aa + j * 64 + 32); a[2] = lds32(aa + j * 64 + 48);
            mma16816(c, a, b[2], b[3]);
        }
        if (g < 2) stsf2(sb + OFF_RED + ((warp * 2 + g) * 8 + 2 * t) * 4, c[0], c[1]);
        float d0 = bflo(xw0) - mean0, d1 = bfhi(xw0) - mean0, d2 = bflo(xw1) - mean1, d3 = bfhi(xw1) - mean1;
        float v0 = warp_sum(d0 * d0 + d1 * d1), v1 = warp_sum(d2 * d2 + d3 * d3);
        if (lane == 0) stsf2(sb + OFF_SM + 64 + warp * 8, v0, v1);
    }
    bar_compute();
    if (tid < 8) {
        float s0 = 0.f, s1 = 0.f;
#pragma unroll
        for (int w = 0; w < 8; w++) { s0 += ldsf(sb + OFF_RED + (w * 16 + tid) * 4); s1 += ldsf(sb + OFF_RED + (w * 16 + 8 + tid) * 4); }
        str1(gs->e0 + cta * 8 + tid, tagw(pack2(s0, s1), tag));
    }
    TLREC(1);
    {
        const unsigned tw0 = (unsigned)clock();
        float v0 = 0.f, v1 = 0.f;
#pragma unroll
        for (int w = 0; w < 8; w++) { float2 v = ldsf2(sb + OFF_SM + 64 + w * 8); v0 += v.x; v1 += v.y; }
        const float r0 = rsqrtf(v0 * (1.f / 512.f) + 1e-5f), r1 = rsqrtf(v1 * (1.f / 512.f) + 1e-5f);
        const uint32_t* ps = gs->e0 + rank * 256 + tid;
        uint32_t sa, ca, n = 0;
        hold(tw0, D_E0);
        do { sa = ldr1(ps); ca = ldr1(ps + 512); } while (!(ok1(sa, tag) && ok1(ca, tag)) && ++n < SPIN_LIMIT);
        const float h0 = (xh0 - mean0) * r0 * (1.f + bflo(ca)) + bflo(sa);
        const float h1 = (xh1 - mean1) * r1 * (1.f + bfhi(ca)) + bfhi(sa);
        const uint32_t hw = pack2(h0, h1);
        sts16(sb + OFF_ACT + tid * 2, (uint16_t)(hw & 0xffff));
        sts16(sb + OFF_ACT + ACT_PITCH + tid * 2, (uint16_t)(hw >> 16));
    }
    asm volatile("barrier.cluster.wait.aligned;" ::: "memory");
    bar_compute();
    TLREC(2);
    mbar_wait(BAR(B_WQ));
    TLREC(3);
    gemv_pair(sb, sb + OFF_B, OFF_QRED, B_QRED, warp, lane, rank);
    mbar_wait(BAR(B_QRED));
    if (tid == 0) mbar_arrive(BAR(B_FREEB));
    if (tid < 64) {
        const int b = tid >> 5, k2 = tid & 31;
        float s0 = 0.f, s1 = 0.f;
#pragma unroll
        for (int s = 0; s < 4; s++) { float2 v = ldsf2(sb + OFF_QRED + ((s * 2 + b) * 64 + 2 * k2) * 4); s0 += v.x; s1 += v.y; }
        sts32(sb + OFF_ACT + b * ACT_PITCH + k2 * 4, pack2(s0, s1));
    }
    bar_compute();
    TLREC(4);
    mbar_wait(BAR(B_WUK));
    TLREC(5);
    {
        uint32_t bf[8];
        const uint32_t ab = sb + OFF_ACT + (g & 1) * ACT_PITCH + t * 4;
#pragma unroll
        for (int ks = 0; ks < 4; ks++) { bf[2 * ks] = lds32(ab + ks * 32); bf[2 * ks + 1] = lds32(ab + ks * 32 + 16); }
#pragma unroll
        for (int mi = 0; mi < 2; mi++) {
            const int m = (warp * 2 + mi) * 16 + (q4 & 1) * 8 + (lane & 7);
            float c[4] = {0.f, 0.f, 0.f, 0.f};
#pragma unroll
            for (int ks = 0; ks < 4; ks++) {
                uint32_t a[4];
                ldsm4(a, sb + OFF_C + m * 128 + (((2 * ks + (q4 >> 1)) ^ (lane & 7)) << 4));
                mma16816(c, a, bf[2 * ks], bf[2 * ks + 1]);
            }
            const float v = (t & 2) ? ((t & 1) ? c[3] : c[2]) : ((t & 1) ? c[1] : c[0]);
            const uint32_t w = pack2(v, 0.f);
            sts16(sb + OFF_RED + (t & 1) * 512 + ((warp * 2 + mi) * 16 + (t >> 1) * 8 + g) * 2, (uint16_t)(w & 0xffff));
        }
    }
    __syncwarp();
    if (lane == 0) {
        asm volatile("mbarrier.arrive.relaxed.cluster.shared::cluster.b64 _, [%0];" ::"r"(mapa(BAR(B_PEERC), rank ^ 1)) : "memory");
    }
    if (lane < 8) {
        const int b = lane >> 2;
        uint4 v = lds128(sb + OFF_RED + b * 512 + warp * 64 + (lane & 3) * 16);
        v.x = tagw(v.x, tag); v.y = tagw(v.y, tag); v.z = tagw(v.z, tag); v.w = tagw(v.w, tag);
        str4(gs->e1 + (((b * 2 + rank) * 2 + pp) * 32 + hh) * 128 + warp * 16 + (lane & 3) * 4, v);
    }
    TLREC(6);
    {
        const uint32_t* base = gs->e1 + ((ab_ * 2 + rank) * 2) * 32 * 128 + warp * 4 * 128;
        hold((unsigned)clock(), D_E1);
        uint4 v[8];
        uint32_t n = 0;
        bool ok;
#pragma unroll
        for (int j = 0; j < 8; j++) v[j] = ldr4(base + (j & 1) * 32 * 128 + (j >> 1) * 128 + lane * 4);
        do {
            ok = true;
#pragma unroll
            for (int j = 0; j < 8; j++)
                if (!ok4(v[j], tag)) { v[j] = ldr4(base + (j & 1) * 32 * 128 + (j >> 1) * 128 + lane * 4); ok = false; }
        } while (!ok && ++n < SPIN_LIMIT);
#pragma unroll
        for (int j = 0; j < 4; j++) {
            const uint4 a = v[2 * j], b = v[2 * j + 1];
            uint4 o;
            o.x = pack2(bflo(a.x) + bflo(b.x), bfhi(a.x) + bfhi(b.x));
            o.y = pack2(bflo(a.y) + bflo(b.y), bfhi(a.y) + bfhi(b.y));
            o.z = pack2(bflo(a.z) + bflo(b.z), bfhi(a.z) + bfhi(b.z));
            o.w = pack2(bflo(a.w) + bflo(b.w), bfhi(a.w) + bfhi(b.w));
            const int head = warp * 4 + j;
            sts128(sb + OFF_E + (lane >> 3) * 4096 + head * 128 + (((lane & 7) ^ (head & 7)) << 4), o);
        }
    }
    asm volatile("fence.proxy.async.shared::cta;" ::: "memory");
    mbar_wait(BAR(B_PEERC));
    asm volatile("bar.sync 3, 288;" ::: "memory");
    TLREC(7);
    const int wg = warp >> 2, wi = warp & 3, tw = tid & 127;
    {
        constexpr float SC = 0.08838834764831845f * 1.4426950408889634f;
        float o0[16], o1[16], lsum[8], mold[8];
        const uint32_t dA = desclo(sb + OFF_A), dD = desclo(sb + OFF_D), dE = desclo(sb + OFF_E);
#pragma unroll
        for (int i = 0; i < 8; i++) { lsum[i] = 0.f; mold[i] = 0.f; }
#pragma unroll
        for (int i = 0; i < 16; i++) { o0[i] = 0.f; o1[i] = 0.f; }
#pragma unroll 1
        for (int s = 0; s < 2; s++) {
            const int ch = 2 * s + wg;
            float sacc[16];
            mbar_wait(BAR(B_KV0 + ch));
            TLREC1(8 + (s == 0) * 2);
            wg_fence();
#pragma unroll
            for (int cb = 0; cb < 4; cb++)
#pragma unroll
                for (int ks = 0; ks < 4; ks++)
                    wgmma_n32<0>(sacc, dA + ch * 2048 + cb * 512 + ks * 2, dE + cb * 256 + ks * 2, (cb | ks) != 0);
            wg_commit();
            if (s) mbar_wait(BAR(B_SFREE));
            wg_wait0();
            reg_fence(sacc);
            TLREC1(26);
            {
                const uint32_t so = OFF_C + wg * 8192 + tw * 16;
                const uint32_t ra = mapa(sb + so, rank ^ 1), rb = mapa(BAR(B_S0 + ch), rank ^ 1);
#pragma unroll
                for (int j = 0; j < 4; j++) st_async128(ra + j * 2048, sacc[4 * j], sacc[4 * j + 1], sacc[4 * j + 2], sacc[4 * j + 3], rb);
                mbar_wait(BAR(B_S0 + ch));
#pragma unroll
                for (int j = 0; j < 4; j++) {
                    const float4 p = ldsf4(sb + so + j * 2048);
                    sacc[4 * j] = (sacc[4 * j] + p.x) * SC; sacc[4 * j + 1] = (sacc[4 * j + 1] + p.y) * SC;
                    sacc[4 * j + 2] = (sacc[4 * j + 2] + p.z) * SC; sacc[4 * j + 3] = (sacc[4 * j + 3] + p.w) * SC;
                }
                TLREC1(27);
                float mx[8];
#pragma unroll
                for (int j = 0; j < 4; j++) { mx[2 * j] = fmaxf(sacc[4 * j], sacc[4 * j + 2]); mx[2 * j + 1] = fmaxf(sacc[4 * j + 1], sacc[4 * j + 3]); }
                const bool u4 = lane & 16, u2 = lane & 8, u1 = lane & 4;
                float y[4], z[2];
#pragma unroll
                for (int i = 0; i < 4; i++) { const float keep = u4 ? mx[i + 4] : mx[i], send = u4 ? mx[i] : mx[i + 4]; y[i] = fmaxf(keep, __shfl_xor_sync(0xffffffffu, send, 16)); }
#pragma unroll
                for (int i = 0; i < 2; i++) { const float keep = u2 ? y[i + 2] : y[i], send = u2 ? y[i] : y[i + 2]; z[i] = fmaxf(keep, __shfl_xor_sync(0xffffffffu, send, 8)); }
                const float keep = u1 ? z[1] : z[0], send = u1 ? z[0] : z[1];
                const float r = fmaxf(keep, __shfl_xor_sync(0xffffffffu, send, 4));
                int key = __float_as_int(r);
                key = key >= 0 ? key : key ^ 0x7fffffff;
                const int head = 8 * (g >> 1) + 2 * t + (g & 1);
                asm volatile("red.shared.max.s32 [%0], %1;" ::"r"(sb + OFF_SM + 256 + head * 4), "r"(key) : "memory");
                if (s == 0 && lane == 0)
                    asm volatile("mbarrier.arrive.relaxed.cluster.shared::cluster.b64 _, [%0];" ::"r"(mapa(BAR(B_SFREE), rank ^ 1)) : "memory");
            }
            bar_compute();
            TLREC1(28);
            float mnew[8], alpha[8];
#pragma unroll
            for (int j = 0; j < 4; j++) {
                const float2 kk = ldsf2(sb + OFF_SM + 256 + (8 * j + 2 * t) * 4);
                int k0 = __float_as_int(kk.x), k1 = __float_as_int(kk.y);
                k0 = k0 >= 0 ? k0 : k0 ^ 0x7fffffff; k1 = k1 >= 0 ? k1 : k1 ^ 0x7fffffff;
                mnew[2 * j] = __int_as_float(k0); mnew[2 * j + 1] = __int_as_float(k1);
            }
            {
                uint32_t pk[8];
#pragma unroll
                for (int j = 0; j < 4; j++) {
                    const float p0 = ex2(sacc[4 * j] - mnew[2 * j]), p1 = ex2(sacc[4 * j + 1] - mnew[2 * j + 1]);
                    const float p2 = ex2(sacc[4 * j + 2] - mnew[2 * j]), p3 = ex2(sacc[4 * j + 3] - mnew[2 * j + 1]);
                    pk[2 * j] = pack2(p0, p1); pk[2 * j + 1] = pack2(p2, p3);
                }
                const int hrow = (q4 >> 1) * 8 + (lane & 7);
                const uint32_t pa = sb + OFF_D + wg * 4096 + hrow * 128 + (((2 * wi + (q4 & 1)) ^ (lane & 7)) << 4);
                stsm4t(pa, pk[0], pk[1], pk[2], pk[3]);
                stsm4t(pa + 2048, pk[4], pk[5], pk[6], pk[7]);
                asm volatile("fence.proxy.async.shared::cta;" ::: "memory");
#pragma unroll
                for (int j = 0; j < 4; j++) {
                    sacc[2 * j] = bflo(pk[2 * j]) + bflo(pk[2 * j + 1]);
                    sacc[2 * j + 1] = bfhi(pk[2 * j]) + bfhi(pk[2 * j + 1]);
                }
            }
            if (s) {
#pragma unroll
                for (int i = 0; i < 8; i++) { alpha[i] = ex2(mold[i] - mnew[i]); lsum[i] = lsum[i] * alpha[i] + sacc[i]; }
#pragma unroll
                for (int j = 0; j < 4; j++) {
                    o0[4 * j] *= alpha[2 * j]; o0[4 * j + 1] *= alpha[2 * j + 1]; o0[4 * j + 2] *= alpha[2 * j]; o0[4 * j + 3] *= alpha[2 * j + 1];
                    o1[4 * j] *= alpha[2 * j]; o1[4 * j + 1] *= alpha[2 * j + 1]; o1[4 * j + 2] *= alpha[2 * j]; o1[4 * j + 3] *= alpha[2 * j + 1];
                }
            } else {
#pragma unroll
                for (int i = 0; i < 8; i++) { mold[i] = mnew[i]; lsum[i] = sacc[i]; }
            }
            mbar_wait(BAR(B_KV0 + (ch ^ 1)));
            bar_compute();
            TLREC1(29);
            wg_fence();
#pragma unroll
            for (int ks = 0; ks < 8; ks++) {
                const uint32_t ka = dA + (s * 2 + (ks >> 2)) * 2048 + wg * 1024 + (ks & 3) * 128;
                const uint32_t db = dD + (ks >> 2) * 256 + (ks & 3) * 2;
                wgmma_n32<1>(o0, ka, db, 1);
                wgmma_n32<1>(o1, ka + 512, db, 1);
            }
            wg_commit();
            if (s == 1) {
                const bool u4 = lane & 16, u2 = lane & 8, u1 = lane & 4;
                float y[4], z[2];
#pragma unroll
                for (int i = 0; i < 4; i++) { const float keep = u4 ? lsum[i + 4] : lsum[i], send = u4 ? lsum[i] : lsum[i + 4]; y[i] = keep + __shfl_xor_sync(0xffffffffu, send, 16); }
#pragma unroll
                for (int i = 0; i < 2; i++) { const float keep = u2 ? y[i + 2] : y[i], send = u2 ? y[i] : y[i + 2]; z[i] = keep + __shfl_xor_sync(0xffffffffu, send, 8); }
                const float keep = u1 ? z[1] : z[0], send = u1 ? z[0] : z[1];
                const float r = keep + __shfl_xor_sync(0xffffffffu, send, 4);
                const int head = 8 * (g >> 1) + 2 * t + (g & 1);
                asm volatile("red.shared.add.f32 [%0], %1;" ::"r"(sb + OFF_SM + 384 + head * 4), "f"(r) : "memory");
            }
            wg_wait0();
            reg_fence(o0); reg_fence(o1);
            if (lane == 0) {
                mbar_arrive(BAR(s ? B_FREEA2 : B_FREEA0));
                if (s) asm volatile("mbarrier.arrive.relaxed.cluster.shared::cluster.b64 _, [%0];" ::"r"(mapa(BAR(B_FREEA2), rank ^ 1)) : "memory");
            }
            TLREC1(9 + (s == 0) * 21);
        }
        TLREC(31);
        {
            const int hrow = (q4 >> 1) * 8 + (lane & 7);
#pragma unroll
            for (int mi = 0; mi < 2; mi++) {
                const float(&o)[16] = mi ? o1 : o0;
                const int chunk = (wg * 2 + mi) * 8 + wi * 2 + (q4 & 1);
                const uint32_t a = sb + OFF_E + hrow * 512 + ((chunk ^ (lane & 7)) << 4);
                stsm4t(a, pack2(o[0], o[1]), pack2(o[2], o[3]), pack2(o[4], o[5]), pack2(o[6], o[7]));
                stsm4t(a + 16 * 512, pack2(o[8], o[9]), pack2(o[10], o[11]), pack2(o[12], o[13]), pack2(o[14], o[15]));
            }
        }
    }
    bar_compute();
    TLREC(11);
    {
        const int part = ab_ * 32 + kb;
        if (lane < 8) {
            const int head = warp * 4 + (lane >> 1);
            int k = (int)lds32(sb + OFF_SM + 256 + head * 4);
            k = k >= 0 ? k : k ^ 0x7fffffff;
            const uint32_t m = tagw((uint32_t)k, tag), l = tagw(lds32(sb + OFF_SM + 384 + head * 4), tag);
            str4(gs->ml + ((head * 2 + rank) * 64 + part) * 8 + (lane & 1) * 4, make_uint4(m, l, m, l));
        }
#pragma unroll
        for (int j = 0; j < 4; j++) {
            const int head = warp * 4 + j;
            uint4 v = lds128(sb + OFF_E + head * 512 + ((lane ^ (head & 7)) << 4));
            v.x = tagw(v.x, tag); v.y = tagw(v.y, tag); v.z = tagw(v.z, tag); v.w = tagw(v.w, tag);
            str4(gs->e2 + ((head * 4 + rank * 2 + (lane >> 4)) * 64 + part) * 64 + (lane & 15) * 4, v);
        }
        TLREC(21);
    }
    TLREC(12);
    uint32_t wf[8][4];
    {
        const unsigned tw0 = (unsigned)clock();
        const int b = warp >> 2, ph = warp & 1;
        const uint32_t* pml = gs->ml + ((hh * 2 + pp) * 64 + b * 32 + lane) * 8;
        const uint32_t* pd = gs->e2 + ((hh * 4 + (cta & 3)) * 64 + b * 32 + ph * 16 + q4) * 64 + (warp & 2) * 16 + (lane & 7) * 4;
        uint2 ml = make_uint2(~tag, ~tag);
        uint4 v[4];
#pragma unroll
        for (int j = 0; j < 4; j++) v[j] = make_uint4(~tag, ~tag, ~tag, ~tag);
        mbar_wait(BAR(B_WUV));
        {
            const int kr = (q4 >> 1) * 8 + (lane & 7);
            const uint32_t wa = sb + OFF_B + (warp >> 2) * 16384 + kr * 128 + (((2 * (warp & 3) + (q4 & 1)) ^ (lane & 7)) << 4);
#pragma unroll
            for (int ks = 0; ks < 8; ks++) ldsm4t(wf[ks], wa + ks * 2048);
        }
        hold(tw0, D_E2);
        uint32_t n = 0;
        bool ok;
        do {
            if (!ok2(ml, tag)) ml = ldr2(pml);
#pragma unroll
            for (int j = 0; j < 4; j++) if (!ok4(v[j], tag)) v[j] = ldr4(pd + j * 4 * 64);
            ok = ok2(ml, tag) && ok4(v[0], tag) && ok4(v[1], tag) && ok4(v[2], tag) && ok4(v[3], tag);
        } while (!ok && ++n < SPIN_LIMIT);
        __syncwarp();
        const float m = __uint_as_float(ml.x);
        float M = m;
#pragma unroll
        for (int o = 16; o; o >>= 1) M = fmaxf(M, __shfl_xor_sync(0xffffffffu, M, o));
        float w = ex2(m - M);
        const float L = warp_sum(w * __uint_as_float(ml.y));
        float a[8];
#pragma unroll
        for (int i = 0; i < 8; i++) a[i] = 0.f;
#pragma unroll
        for (int j = 0; j < 4; j++) {
            const float wj = __shfl_sync(0xffffffffu, w, ph * 16 + j * 4 + q4);
            a[0] += wj * bflo(v[j].x); a[1] += wj * bfhi(v[j].x); a[2] += wj * bflo(v[j].y); a[3] += wj * bfhi(v[j].y);
            a[4] += wj * bflo(v[j].z); a[5] += wj * bfhi(v[j].z); a[6] += wj * bflo(v[j].w); a[7] += wj * bfhi(v[j].w);
        }
        const bool u4 = lane & 16, u2 = lane & 8;
        float y[4], z[2];
#pragma unroll
        for (int i = 0; i < 4; i++) { const float keep = u4 ? a[i + 4] : a[i], send = u4 ? a[i] : a[i + 4]; y[i] = keep + __shfl_xor_sync(0xffffffffu, send, 16); }
#pragma unroll
        for (int i = 0; i < 2; i++) { const float keep = u2 ? y[i + 2] : y[i], send = u2 ? y[i] : y[i + 2]; z[i] = keep + __shfl_xor_sync(0xffffffffu, send, 8); }
        const float rl = __fdividef(1.f, L);
        sts32(sb + OFF_ACT + (ph * 2 + b) * 272 + ((warp & 2) * 32 + (lane & 7) * 8 + q4 * 2) * 2, pack2(z[0] * rl, z[1] * rl));
    }
    bar_compute();
    TLREC(13);
    {
        float c[4] = {0.f, 0.f, 0.f, 0.f}, c2[4] = {0.f, 0.f, 0.f, 0.f};
        const uint32_t ab = sb + OFF_ACT + (lane & 3) * 272 + q4 * 16;
#pragma unroll
        for (int ks = 0; ks < 8; ks += 2) {
            uint32_t bq[4];
            ldsm4(bq, ab + ks * 32);
            mma16816(c, wf[ks], bq[0], bq[1]);
            mma16816(c2, wf[ks + 1], bq[2], bq[3]);
        }
        float x = (t & 2) ? c[2] + c2[2] : c[0] + c2[0], y = (t & 2) ? c[3] + c2[3] : c[1] + c2[1];
        x += __shfl_xor_sync(0xffffffffu, x, 1); y += __shfl_xor_sync(0xffffffffu, y, 1);
        if (!(t & 1)) str1(gs->x1 + (cta & 3) * 4096 + hh * 128 + warp * 16 + (t >> 1) * 8 + g, tagw(pack2(x, y), tag));
    }
    TLREC(14);
    {
        const unsigned tw0 = (unsigned)clock();
        const uint32_t* px = gs->x1 + kq * 1024 + tid * 4;
        mbar_wait(BAR(B_WO));
        {
            const int kr = warp * 128 + (q4 >> 1) * 8 + (lane & 7);
            const uint32_t wa = sb + OFF_WO + kr * 32 + (((q4 & 1) ^ ((kr >> 2) & 1)) << 4);
#pragma unroll
            for (int ks = 0; ks < 8; ks++) ldsm4t(wf[ks], wa + ks * 512);
        }
        uint4 u[4];
        uint32_t n = 0;
        bool ok;
#pragma unroll
        for (int j = 0; j < 4; j++) u[j] = make_uint4(~tag, ~tag, ~tag, ~tag);
        hold(tw0, D_X1);
        do {
#pragma unroll
            for (int j = 0; j < 4; j++) if (!ok4(u[j], tag)) u[j] = ldr4(px + j * 4096);
            ok = ok4(u[0], tag) && ok4(u[1], tag) && ok4(u[2], tag) && ok4(u[3], tag);
        } while (!ok && ++n < SPIN_LIMIT);
        const uint32_t da = sb + OFF_D + tid * 8;
        sts64(da, pack2((bflo(u[0].x) + bflo(u[1].x)) + (bflo(u[2].x) + bflo(u[3].x)), (bflo(u[0].y) + bflo(u[1].y)) + (bflo(u[2].y) + bflo(u[3].y))),
              pack2((bflo(u[0].z) + bflo(u[1].z)) + (bflo(u[2].z) + bflo(u[3].z)), (bflo(u[0].w) + bflo(u[1].w)) + (bflo(u[2].w) + bflo(u[3].w))));
        sts64(da + ACTL_PITCH, pack2((bfhi(u[0].x) + bfhi(u[1].x)) + (bfhi(u[2].x) + bfhi(u[3].x)), (bfhi(u[0].y) + bfhi(u[1].y)) + (bfhi(u[2].y) + bfhi(u[3].y))),
              pack2((bfhi(u[0].z) + bfhi(u[1].z)) + (bfhi(u[2].z) + bfhi(u[3].z)), (bfhi(u[0].w) + bfhi(u[1].w)) + (bfhi(u[2].w) + bfhi(u[3].w))));
    }
    uint2 ga = ldr2(gs->m2 + 2 * tid), sbv = ldr2(gs->m2 + 512 + 2 * tid), cbv = ldr2(gs->m2 + 1024 + 2 * tid);
    uint32_t gbw = ldr1(gs->m2 + 1536 + (cta & 63) * 8 + (tid & 7));
    __syncwarp();
    TLREC(15);
    {
        float c[4] = {0.f, 0.f, 0.f, 0.f}, c2[4] = {0.f, 0.f, 0.f, 0.f};
        const uint32_t ab = sb + OFF_D + (lane & 1) * ACTL_PITCH + warp * 256 + q4 * 16;
#pragma unroll
        for (int ks = 0; ks < 8; ks += 2) {
            uint32_t bq[4];
            ldsm4(bq, ab + ks * 32);
            mma16816(c, wf[ks], bq[0], bq[1]);
            mma16816(c2, wf[ks + 1], bq[2], bq[3]);
        }
        if (t < 2) stsf2(sb + OFF_RED + (warp * 16 + t * 8 + g) * 8, t ? c[2] + c2[2] : c[0] + c2[0], t ? c[3] + c2[3] : c[1] + c2[1]);
    }
    bar_compute();
    if (tid < 16) {
        float s0 = 0.f, s1 = 0.f;
#pragma unroll
        for (int w = 0; w < 8; w++) { float2 v = ldsf2(sb + OFF_RED + (w * 16 + tid) * 8); s0 += v.x; s1 += v.y; }
        str1(gs->x2 + kq * 512 + cg * 16 + tid, tagw(pack2(s0, s1), tag));
    }
    TLREC(16);
    bool pre;
    const uint32_t wgu = sb + ((warp >> 2) ? OFF_WU : OFF_WG) + ((warp & 3) * 128 + (q4 >> 1) * 8 + (lane & 7)) * 64 + (((rank * 2 + (q4 & 1)) ^ ((lane >> 1) & 3)) << 4);
    {
        const unsigned tw0 = (unsigned)clock();
        uint32_t n = 0;
        while (!(ok2(ga, tag) && ok2(sbv, tag) && ok2(cbv, tag) && ok1(gbw, tag)) && ++n < SPIN_LIMIT) {
            ga = ldr2(gs->m2 + 2 * tid); sbv = ldr2(gs->m2 + 512 + 2 * tid); cbv = ldr2(gs->m2 + 1024 + 2 * tid);
            gbw = ldr1(gs->m2 + 1536 + (cta & 63) * 8 + (tid & 7));
        }
        const float k00 = 1.f + bflo(cbv.x), k01 = 1.f + bflo(cbv.y), k10 = 1.f + bfhi(cbv.x), k11 = 1.f + bfhi(cbv.y);
        sts32(sb + OFF_E + 2 * ACT_PITCH + tid * 4, pack2(k00, k01));
        sts32(sb + OFF_E + 3 * ACT_PITCH + tid * 4, pack2(k10, k11));
        sts32(sb + OFF_E + 4 * ACT_PITCH + tid * 4, __byte_perm(sbv.x, sbv.y, 0x5410));
        sts32(sb + OFF_E + 5 * ACT_PITCH + tid * 4, __byte_perm(sbv.x, sbv.y, 0x7632));
        uint2 p[4];
        bool ok;
        n = 0;
        pre = cta < NFFN && __all_sync(0xffffffffu, mbar_test(BAR((warp >> 2) ? B_WU : B_WG)));
        if (pre) {
#pragma unroll
            for (int ks = 0; ks < 8; ks++) ldsm4t(wf[ks], wgu + ks * 1024);
        }
#pragma unroll
        for (int j = 0; j < 4; j++) p[j] = make_uint2(~tag, ~tag);
        hold(tw0, D_X2);
        do {
#pragma unroll
            for (int j = 0; j < 4; j++) if (!ok2(p[j], tag)) p[j] = ldr2(gs->x2 + j * 512 + 2 * tid);
            ok = ok2(p[0], tag) && ok2(p[1], tag) && ok2(p[2], tag) && ok2(p[3], tag);
        } while (!ok && ++n < SPIN_LIMIT);
        const float a00 = (bflo(p[0].x) + bflo(p[1].x)) + (bflo(p[2].x) + bflo(p[3].x));
        const float a10 = (bfhi(p[0].x) + bfhi(p[1].x)) + (bfhi(p[2].x) + bfhi(p[3].x));
        const float a01 = (bflo(p[0].y) + bflo(p[1].y)) + (bflo(p[2].y) + bflo(p[3].y));
        const float a11 = (bfhi(p[0].y) + bfhi(p[1].y)) + (bfhi(p[2].y) + bfhi(p[3].y));
        const float y00 = bflo(xw0) + bflo(ga.x) * a00, y01 = bfhi(xw0) + bflo(ga.y) * a01;
        const float y10 = bflo(xw1) + bfhi(ga.x) * a10, y11 = bfhi(xw1) + bfhi(ga.y) * a11;
        sts32(sb + OFF_E + tid * 4, pack2(y00 * k00, y01 * k01));
        sts32(sb + OFF_E + ACT_PITCH + tid * 4, pack2(y10 * k10, y11 * k11));
        if ((tid >> 2) == (cta & 63)) stsf2(sb + OFF_SM + 192 + (tid & 3) * 8, ab_ ? y10 : y00, ab_ ? y11 : y01);
        const bool u4 = lane & 16, u2 = lane & 8;
        const float s0 = y00 + y01, s1 = y10 + y11, q0 = y00 * y00 + y01 * y01, q1 = y10 * y10 + y11 * y11;
        const float r0 = (u4 ? q0 : s0) + __shfl_xor_sync(0xffffffffu, u4 ? s0 : q0, 16);
        const float r1 = (u4 ? q1 : s1) + __shfl_xor_sync(0xffffffffu, u4 ? s1 : q1, 16);
        float r = (u2 ? r1 : r0) + __shfl_xor_sync(0xffffffffu, u2 ? r0 : r1, 8);
        r += __shfl_xor_sync(0xffffffffu, r, 4); r += __shfl_xor_sync(0xffffffffu, r, 2); r += __shfl_xor_sync(0xffffffffu, r, 1);
        if (!(lane & 7)) stsf(sb + OFF_SM + warp * 16 + (lane >> 3) * 4, r);
    }
    bar_compute();
    TLREC(17);
    if (cta < NFFN) {
        if (!pre) {
            mbar_wait(BAR((warp >> 2) ? B_WU : B_WG));
#pragma unroll
            for (int ks = 0; ks < 8; ks++) ldsm4t(wf[ks], wgu + ks * 1024);
        }
        {
            float c[4] = {0.f, 0.f, 0.f, 0.f}, c2[4] = {0.f, 0.f, 0.f, 0.f};
            const int br = lane & 7;
            const uint32_t ab = sb + OFF_E + (br < 6 ? br : br - 6) * ACT_PITCH + (warp & 3) * 256 + q4 * 16;
#pragma unroll
            for (int ks = 0; ks < 8; ks += 2) {
                uint32_t bq[4];
                ldsm4(bq, ab + ks * 32);
                mma16816(c, wf[ks], bq[0], bq[1]);
                mma16816(c2, wf[ks + 1], bq[2], bq[3]);
            }
            float4 st = make_float4(0.f, 0.f, 0.f, 0.f);
#pragma unroll
            for (int w = 0; w < 8; w++) { const float4 v = ldsf4(sb + OFF_SM + w * 16); st.x += v.x; st.y += v.y; st.z += v.z; st.w += v.w; }
            const float m0 = st.x * (1.f / 512.f), m1 = st.y * (1.f / 512.f);
            const float r0 = rsqrtf(fmaxf(st.z * (1.f / 512.f) - m0 * m0, 0.f) + 1e-5f), r1 = rsqrtf(fmaxf(st.w * (1.f / 512.f) - m1 * m1, 0.f) + 1e-5f);
            const float f0 = t == 0 ? r0 : (t == 1 ? -r0 * m0 : (t == 2 ? 1.f : 0.f));
            const float f1 = t == 0 ? r1 : (t == 1 ? -r1 * m1 : (t == 2 ? 1.f : 0.f));
            const float e0 = (c[0] + c2[0]) * f0, e1 = (c[1] + c2[1]) * f1, e2 = (c[2] + c2[2]) * f0, e3 = (c[3] + c2[3]) * f1;
            const bool w2 = t & 2, w1 = t & 1;
            const float h0 = (w2 ? e2 : e0) + __shfl_xor_sync(0xffffffffu, w2 ? e0 : e2, 2);
            const float h1 = (w2 ? e3 : e1) + __shfl_xor_sync(0xffffffffu, w2 ? e1 : e3, 2);
            const float v = (w1 ? h1 : h0) + __shfl_xor_sync(0xffffffffu, w1 ? h0 : h1, 1);
            stsf(sb + OFF_RED + ((warp * 2 + (t & 1)) * 16 + (t >> 1) * 8 + g) * 4, v);
        }
        mbar_wait(BAR(B_WD));
#pragma unroll
        for (int mi = 0; mi < 4; mi++)
            ldsm4t(wf[mi], sb + OFF_WD + warp * 2048 + ((q4 >> 1) * 8 + (lane & 7)) * 128 + (((2 * mi + (q4 & 1)) ^ (lane & 7)) << 4));
        bar_compute();
        uint32_t b0, b1;
        {
            float gv[4] = {0.f, 0.f, 0.f, 0.f}, uv[4] = {0.f, 0.f, 0.f, 0.f};
            const uint32_t ra = sb + OFF_RED + ((g & 1) * 16 + 2 * t) * 4;
#pragma unroll
            for (int s = 0; s < 4; s++) {
                const float2 x0 = ldsf2(ra + s * 128), x1 = ldsf2(ra + s * 128 + 32);
                const float2 y0 = ldsf2(ra + 512 + s * 128), y1 = ldsf2(ra + 512 + s * 128 + 32);
                gv[0] += x0.x; gv[1] += x0.y; gv[2] += x1.x; gv[3] += x1.y;
                uv[0] += y0.x; uv[1] += y0.y; uv[2] += y1.x; uv[3] += y1.y;
            }
            b0 = pack2(gelu_tanh(gv[0]) * uv[0], gelu_tanh(gv[1]) * uv[1]);
            b1 = pack2(gelu_tanh(gv[2]) * uv[2], gelu_tanh(gv[3]) * uv[3]);
        }
#pragma unroll
        for (int mi = 0; mi < 4; mi++) {
            float c[4] = {0.f, 0.f, 0.f, 0.f};
            mma16816(c, wf[mi], b0, b1);
            const float v = (t & 2) ? ((t & 1) ? c[3] : c[2]) : ((t & 1) ? c[1] : c[0]);
            const int cons = (t & 1) * 64 + warp * 8 + mi * 2 + (t >> 1);
            str1(gs->e4 + (cons * NFFN + cta) * 8 + g, tagw(__float_as_uint(v), tag));
        }
    }
    TLREC(18);
    if (warp < 7) {
        const uint32_t* pe = gs->e4 + cta * NFFN * 8 + tid * 4;
        uint4 v;
        uint32_t n = 0;
        hold((unsigned)clock(), D_E4);
        do { v = ldr4(pe); } while (!ok4(v, tag) && ++n < SPIN_LIMIT);
        __syncwarp();
        float f0 = __uint_as_float(v.x), f1 = __uint_as_float(v.y), f2 = __uint_as_float(v.z), f3 = __uint_as_float(v.w);
#pragma unroll
        for (int o = 2; o <= 16; o <<= 1) {
            f0 += __shfl_xor_sync(0xffffffffu, f0, o); f1 += __shfl_xor_sync(0xffffffffu, f1, o);
            f2 += __shfl_xor_sync(0xffffffffu, f2, o); f3 += __shfl_xor_sync(0xffffffffu, f3, o);
        }
        if (lane < 2) { stsf2(sb + OFF_CRED + warp * 32 + lane * 16, f0, f1); stsf2(sb + OFF_CRED + warp * 32 + lane * 16 + 8, f2, f3); }
    }
    bar_compute();
    if (tid < 8) {
        float s = 0.f;
#pragma unroll
        for (int w = 0; w < 7; w++) s += ldsf(sb + OFF_CRED + w * 32 + tid * 4);
        const float gb = ab_ ? bfhi(gbw) : bflo(gbw);
        gout[cta * 8 + tid] = __float2bfloat16(ldsf(sb + OFF_SM + 192 + tid * 4) + gb * s);
        if (cta == 0 && tid == 0) str1(gs->epoch, epoch + 1);
    }
    TLREC(19);
}

typedef CUresult (*EncodeFn)(CUtensorMap*, CUtensorMapDataType, cuuint32_t, void*, const cuuint64_t*, const cuuint64_t*,
                             const cuuint32_t*, const cuuint32_t*, CUtensorMapInterleave, CUtensorMapSwizzle,
                             CUtensorMapL2promotion, CUtensorMapFloatOOBfill);

void enc2d(EncodeFn f, CUtensorMap* m, const void* p, uint64_t cols, uint64_t rows, uint32_t bc, uint32_t br, CUtensorMapSwizzle sw) {
    cuuint64_t dims[2] = {cols, rows};
    cuuint64_t strides[1] = {cols * 2};
    cuuint32_t box[2] = {bc, br}, es[2] = {1, 1};
    f(m, CU_TENSOR_MAP_DATA_TYPE_BFLOAT16, 2, const_cast<void*>(p), dims, strides, box, es, CU_TENSOR_MAP_INTERLEAVE_NONE, sw,
      CU_TENSOR_MAP_L2_PROMOTION_NONE, CU_TENSOR_MAP_FLOAT_OOB_FILL_NONE);
}
void enc3d(EncodeFn f, CUtensorMap* m, const void* p, uint64_t rows, uint32_t br, uint32_t bb) {
    cuuint64_t dims[3] = {64, rows, 8};
    cuuint64_t strides[2] = {1024, 128};
    cuuint32_t box[3] = {64, br, bb}, es[3] = {1, 1, 1};
    f(m, CU_TENSOR_MAP_DATA_TYPE_BFLOAT16, 3, const_cast<void*>(p), dims, strides, box, es, CU_TENSOR_MAP_INTERLEAVE_NONE,
      CU_TENSOR_MAP_SWIZZLE_128B, CU_TENSOR_MAP_L2_PROMOTION_NONE, CU_TENSOR_MAP_FLOAT_OOB_FILL_NONE);
}

}

extern "C" void kernel_launch(void* const* d_in, const int* in_sizes, int n_in, void* d_out, int out_size) {
    (void)in_sizes; (void)n_in; (void)out_size;
    static EncodeFn enc = nullptr;
    static Scratch* scratch = nullptr;
    if (!enc) {
        void* fn = nullptr;
        cudaDriverEntryPointQueryResult qr;
        cudaGetDriverEntryPoint("cuTensorMapEncodeTiled", &fn, cudaEnableDefault, &qr);
        enc = (EncodeFn)fn;
        cudaGetSymbolAddress((void**)&scratch, g_s);
        cudaFuncSetAttribute(fused_kernel, cudaFuncAttributeMaxDynamicSharedMemorySize, SMEM_BYTES);
    }
    Maps m;
    enc2d(enc, &m.wq, d_in[2], 4096, 512, 64, BOXK * 8, CU_TENSOR_MAP_SWIZZLE_128B);
    enc2d(enc, &m.wuk, d_in[3], 4096, 512, 64, BOXK * 8, CU_TENSOR_MAP_SWIZZLE_128B);
    enc2d(enc, &m.wuv, d_in[4], 4096, 512, 64, BOXK * 8, CU_TENSOR_MAP_SWIZZLE_128B);
    enc2d(enc, &m.kv, d_in[1], 512, 16384, 64, BOXK * 8, CU_TENSOR_MAP_SWIZZLE_128B);
    enc2d(enc, &m.wo, d_in[5], 512, 4096, 16, NBOX, CU_TENSOR_MAP_SWIZZLE_32B);
    enc2d(enc, &m.wm, d_in[11], 3072, 512, 32, MBOX, CU_TENSOR_MAP_SWIZZLE_64B);
    enc2d(enc, &m.wg, d_in[7], 1792, 512, 32, MBOX, CU_TENSOR_MAP_SWIZZLE_64B);
    enc2d(enc, &m.wu, d_in[8], 1792, 512, 32, MBOX, CU_TENSOR_MAP_SWIZZLE_64B);
    enc3d(enc, &m.wd, d_in[9], 1792, 16, BOXK / 2);
    fused_kernel<<<NCTA, NTHR, SMEM_BYTES>>>((const __nv_bfloat16*)d_in[0], (const __nv_bfloat16*)d_in[10],
                                             (const __nv_bfloat16*)d_in[11], (__nv_bfloat16*)d_out, scratch, m);
}
```

```cpp
#include <cuda_runtime.h>
#include <cuda_bf16.h>
#include <cuda.h>
#include <stdint.h>

#define D_E0 1250
#define D_E1 1500
#define D_E2 1400
#define D_X1 1000
#define D_X2 1200
#define D_E4 1400
#define BOXK 4
#define MBOX 32
#define STAG 370
#define DSH 60
#define PACE_NUM 1195
#define PACE1_NUM 1050
#define PACE2_NUM 950
#define PACE3_NUM 1400
#define KVGAP 300
#define PAUSE 1700

namespace {

constexpr int NCTA = 128;
constexpr int NTHR = 320;
constexpr int NFFN = 112;
#define SPIN_LOG 20
constexpr uint32_t SPIN_LIMIT = 1u << SPIN_LOG;

constexpr int OFF_A = 0;
constexpr int OFF_B = 131072;
constexpr int OFF_C = 163840;
constexpr int OFF_D = 196608;
constexpr int OFF_E = 204800;
constexpr int OFF_M = 221184;
constexpr int OFF_BAR = OFF_M;
constexpr int OFF_SC = OFF_BAR + 256;
constexpr int OFF_ACT = OFF_SC + 2080;
constexpr int OFF_QRED = OFF_ACT + 2080;
constexpr int OFF_CRED = OFF_QRED + 2048;
constexpr int OFF_RED = OFF_CRED + 2048;
constexpr int OFF_SM = OFF_RED + 1024;
constexpr int SMEM_BYTES = OFF_SM + 512;
static_assert(SMEM_BYTES <= 232448, "smem");
constexpr int ACT_PITCH = 1040;
constexpr int ACTL_PITCH = 2064;
constexpr int OFF_WO = OFF_A;
constexpr int OFF_WG = OFF_B;
constexpr int OFF_WU = OFF_A + 65536;
constexpr int OFF_WD = OFF_A + 98304;
constexpr int OFF_WM2 = OFF_C;

enum { B_WQ = 0, B_WUK, B_KV0, B_KV1, B_KV2, B_KV3, B_WUV, B_WM2, B_WO, B_WG, B_WU, B_WD,
       B_QRED, B_S0, B_S1, B_S2, B_S3, B_FREEB, B_FREEB2, B_FREEA0, B_FREEA2, B_PEERC, B_SFREE, B_COUNT };

struct __align__(1024) Scratch {
    uint32_t e0[1024];
    uint32_t m2[2048];
    uint32_t x2[4 * 512];
    uint32_t x1[4 * 4096];
    uint32_t e1[2 * 2 * 2 * 32 * 128];
    uint32_t ml[32 * 2 * 64 * 8];
    uint32_t e4[128 * NFFN * 8];
    uint32_t e2[32 * 4 * 64 * 64];
    uint32_t epoch[32];
};
__device__ Scratch g_s;
#define TLREC(i)
#define TLREC1(i)
#define TLRECP(i)

struct Maps { CUtensorMap wq, wuk, wuv, kv, wo, wm, wg, wu, wd; };

__device__ __forceinline__ uint32_t smem_u32(const void* p) { return (uint32_t)__cvta_generic_to_shared(p); }
__device__ __forceinline__ void mbar_init(uint32_t bar, uint32_t cnt) { asm volatile("mbarrier.init.shared::cta.b64 [%0], %1;" ::"r"(bar), "r"(cnt) : "memory"); }
__device__ __forceinline__ void mbar_expect(uint32_t bar, uint32_t bytes) { asm volatile("mbarrier.arrive.expect_tx.shared::cta.b64 _, [%0], %1;" ::"r"(bar), "r"(bytes) : "memory"); }
__device__ __forceinline__ void mbar_arrive(uint32_t bar) { asm volatile("mbarrier.arrive.shared::cta.b64 _, [%0];" ::"r"(bar) : "memory"); }
__device__ __forceinline__ bool mbar_try(uint32_t bar) {
    uint32_t ok;
    asm volatile("{\n.reg .pred p;\nmbarrier.try_wait.parity.shared::cta.b64 p, [%1], 0;\nselp.u32 %0, 1, 0, p;\n}\n" : "=r"(ok) : "r"(bar) : "memory");
    return ok;
}
__device__ __forceinline__ bool mbar_test(uint32_t bar) {
    uint32_t ok;
    asm volatile("{\n.reg .pred p;\nmbarrier.test_wait.parity.shared::cta.b64 p, [%1], 0;\nselp.u32 %0, 1, 0, p;\n}\n" : "=r"(ok) : "r"(bar) : "memory");
    return ok;
}
__device__ __forceinline__ void mbar_wait(uint32_t bar) { uint32_t n = 0; while (!mbar_try(bar) && ++n < SPIN_LIMIT) {} }
__device__ __forceinline__ bool elect_one() {
    uint32_t p;
    asm volatile("{\n.reg .pred P;\nelect.sync _|P, 0xffffffff;\nselp.u32 %0,1,0,P;\n}\n" : "=r"(p));
    return p;
}
__device__ __forceinline__ void tma2d(uint32_t dst, const CUtensorMap* m, int c0, int c1, uint32_t bar) {
    asm volatile("cp.async.bulk.tensor.2d.shared::cluster.global.mbarrier::complete_tx::bytes [%0], [%1, {%3, %4}], [%2];"
                 ::"r"(dst), "l"(m), "r"(bar), "r"(c0), "r"(c1) : "memory");
}
__device__ __forceinline__ void tma2d_mc(uint32_t dst, const CUtensorMap* m, int c0, int c1, uint32_t bar) {
    asm volatile("cp.async.bulk.tensor.2d.shared::cluster.global.mbarrier::complete_tx::bytes.multicast::cluster [%0], [%1, {%3, %4}], [%2], %5;"
                 ::"r"(dst), "l"(m), "r"(bar), "r"(c0), "r"(c1), "h"((uint16_t)3) : "memory");
}
__device__ __forceinline__ void tma3d(uint32_t dst, const CUtensorMap* m, int c0, int c1, int c2, uint32_t bar) {
    asm volatile("cp.async.bulk.tensor.3d.shared::cluster.global.mbarrier::complete_tx::bytes [%0], [%1, {%3, %4, %5}], [%2];"
                 ::"r"(dst), "l"(m), "r"(bar), "r"(c0), "r"(c1), "r"(c2) : "memory");
}
__device__ __forceinline__ void bar_compute() { asm volatile("bar.sync 1, 256;" ::: "memory"); }
__device__ __forceinline__ uint32_t mapa(uint32_t addr, uint32_t rank) { uint32_t r; asm("mapa.shared::cluster.u32 %0, %1, %2;" : "=r"(r) : "r"(addr), "r"(rank)); return r; }
__device__ __forceinline__ void st_async32(uint32_t addr, float v, uint32_t bar) {
    asm volatile("st.async.weak.shared::cluster.mbarrier::complete_tx::bytes.f32 [%0], %1, [%2];" ::"r"(addr), "f"(v), "r"(bar) : "memory");
}
__device__ __forceinline__ void st_async128(uint32_t addr, float a, float b, float c, float d, uint32_t bar) {
    asm volatile("st.async.weak.shared::cluster.mbarrier::complete_tx::bytes.v4.f32 [%0], {%1,%2,%3,%4}, [%5];" ::"r"(addr), "f"(a), "f"(b), "f"(c), "f"(d), "r"(bar) : "memory");
}
__device__ __forceinline__ uint32_t ldr1(const uint32_t* p) { uint32_t v; asm volatile("ld.relaxed.gpu.global.u32 %0, [%1];" : "=r"(v) : "l"(p) : "memory"); return v; }
__device__ __forceinline__ uint2 ldr2(const uint32_t* p) { uint2 v; asm volatile("ld.relaxed.gpu.global.v2.u32 {%0,%1}, [%2];" : "=r"(v.x), "=r"(v.y) : "l"(p) : "memory"); return v; }
__device__ __forceinline__ uint4 ldr4(const uint32_t* p) { uint4 v; asm volatile("ld.relaxed.gpu.global.v4.u32 {%0,%1,%2,%3}, [%4];" : "=r"(v.x), "=r"(v.y), "=r"(v.z), "=r"(v.w) : "l"(p) : "memory"); return v; }
__device__ __forceinline__ void str1(uint32_t* p, uint32_t v) { asm volatile("st.relaxed.gpu.global.u32 [%0], %1;" ::"l"(p), "r"(v) : "memory"); }
__device__ __forceinline__ void str4(uint32_t* p, uint4 v) { asm volatile("st.relaxed.gpu.global.v4.u32 [%0], {%1,%2,%3,%4};" ::"l"(p), "r"(v.x), "r"(v.y), "r"(v.z), "r"(v.w) : "memory"); }
__device__ __forceinline__ void ldsm4(uint32_t (&r)[4], uint32_t a) { asm volatile("ldmatrix.sync.aligned.m8n8.x4.shared.b16 {%0,%1,%2,%3}, [%4];" : "=r"(r[0]), "=r"(r[1]), "=r"(r[2]), "=r"(r[3]) : "r"(a) : "memory"); }
__device__ __forceinline__ void ldsm4t(uint32_t (&r)[4], uint32_t a) { asm volatile("ldmatrix.sync.aligned.m8n8.x4.trans.shared.b16 {%0,%1,%2,%3}, [%4];" : "=r"(r[0]), "=r"(r[1]), "=r"(r[2]), "=r"(r[3]) : "r"(a) : "memory"); }
__device__ __forceinline__ void stsm4t(uint32_t a, uint32_t r0, uint32_t r1, uint32_t r2, uint32_t r3) { asm volatile("stmatrix.sync.aligned.m8n8.x4.trans.shared.b16 [%0], {%1,%2,%3,%4};" ::"r"(a), "r"(r0), "r"(r1), "r"(r2), "r"(r3) : "memory"); }
__device__ __forceinline__ void mma16816(float (&c)[4], const uint32_t (&a)[4], uint32_t b0, uint32_t b1) {
    asm volatile("mma.sync.aligned.m16n8k16.row.col.f32.bf16.bf16.f32 {%0,%1,%2,%3}, {%4,%5,%6,%7}, {%8,%9}, {%0,%1,%2,%3};"
                 : "+f"(c[0]), "+f"(c[1]), "+f"(c[2]), "+f"(c[3]) : "r"(a[0]), "r"(a[1]), "r"(a[2]), "r"(a[3]), "r"(b0), "r"(b1));
}
__device__ __forceinline__ uint32_t lds32(uint32_t a) { uint32_t v; asm volatile("ld.shared.u32 %0, [%1];" : "=r"(v) : "r"(a) : "memory"); return v; }
__device__ __forceinline__ float ldsf(uint32_t a) { float v; asm volatile("ld.shared.f32 %0, [%1];" : "=f"(v) : "r"(a) : "memory"); return v; }
__device__ __forceinline__ float2 ldsf2(uint32_t a) { float2 v; asm volatile("ld.shared.v2.f32 {%0,%1}, [%2];" : "=f"(v.x), "=f"(v.y) : "r"(a) : "memory"); return v; }
__device__ __forceinline__ float4 ldsf4(uint32_t a) { float4 v; asm volatile("ld.shared.v4.f32 {%0,%1,%2,%3}, [%4];" : "=f"(v.x), "=f"(v.y), "=f"(v.z), "=f"(v.w) : "r"(a) : "memory"); return v; }
__device__ __forceinline__ uint4 lds128(uint32_t a) { uint4 v; asm volatile("ld.shared.v4.u32 {%0,%1,%2,%3}, [%4];" : "=r"(v.x), "=r"(v.y), "=r"(v.z), "=r"(v.w) : "r"(a) : "memory"); return v; }
__device__ __forceinline__ void sts32(uint32_t a, uint32_t v) { asm volatile("st.shared.u32 [%0], %1;" ::"r"(a), "r"(v) : "memory"); }
__device__ __forceinline__ void sts16(uint32_t a, uint16_t v) { asm volatile("st.shared.u16 [%0], %1;" ::"r"(a), "h"(v) : "memory"); }
__device__ __forceinline__ void stsf(uint32_t a, float v) { asm volatile("st.shared.f32 [%0], %1;" ::"r"(a), "f"(v) : "memory"); }
__device__ __forceinline__ void stsf2(uint32_t a, float x, float y) { asm volatile("st.shared.v2.f32 [%0], {%1,%2};" ::"r"(a), "f"(x), "f"(y) : "memory"); }
__device__ __forceinline__ void sts64(uint32_t a, uint32_t x, uint32_t y) { asm volatile("st.shared.v2.u32 [%0], {%1,%2};" ::"r"(a), "r"(x), "r"(y) : "memory"); }
__device__ __forceinline__ void sts128(uint32_t a, uint4 v) { asm volatile("st.shared.v4.u32 [%0], {%1,%2,%3,%4};" ::"r"(a), "r"(v.x), "r"(v.y), "r"(v.z), "r"(v.w) : "memory"); }
__device__ __forceinline__ uint32_t pack2(float lo, float hi) { uint32_t r; asm("cvt.rn.bf16x2.f32 %0, %1, %2;" : "=r"(r) : "f"(hi), "f"(lo)); return r; }
__device__ __forceinline__ float bflo(uint32_t w) { return __uint_as_float(w << 16); }
__device__ __forceinline__ float bfhi(uint32_t w) { return __uint_as_float(w & 0xffff0000u); }
__device__ __forceinline__ uint32_t tagw(uint32_t w, uint32_t tag) { return (w & ~1u) | tag; }
__device__ __forceinline__ bool ok1(uint32_t v, uint32_t tag) { return ((v ^ tag) & 1u) == 0; }
__device__ __forceinline__ bool ok2(uint2 v, uint32_t tag) { return (((v.x ^ tag) | (v.y ^ tag)) & 1u) == 0; }
__device__ __forceinline__ bool ok4(uint4 v, uint32_t tag) { return (((v.x ^ tag) | (v.y ^ tag) | (v.z ^ tag) | (v.w ^ tag)) & 1u) == 0; }
__device__ __forceinline__ float ex2(float x) { float y; asm("ex2.approx.ftz.f32 %0, %1;" : "=f"(y) : "f"(x)); return y; }
__device__ __forceinline__ float warp_sum(float v) {
#pragma unroll
    for (int o = 16; o; o >>= 1) v += __shfl_xor_sync(0xffffffffu, v, o);
    return v;
}
__device__ __forceinline__ uint32_t desclo(uint32_t addr) { return ((addr & 0x3FFFF) >> 4) | (1u << 16); }
template <int TA>
__device__ __forceinline__ void wgmma_n32(float (&d)[16], uint32_t da, uint32_t db, int acc) {
    asm volatile("{\n.reg .pred p;\n.reg .b64 da, db;\nsetp.ne.b32 p, %18, 0;\n"
                 "mov.b64 da, {%16, %20};\nmov.b64 db, {%17, %20};\n"
                 "wgmma.mma_async.sync.aligned.m64n32k16.f32.bf16.bf16 "
                 "{%0,%1,%2,%3,%4,%5,%6,%7,%8,%9,%10,%11,%12,%13,%14,%15}, da, db, p, 1, 1, %19, 0;\n}\n"
                 : "+f"(d[0]), "+f"(d[1]), "+f"(d[2]), "+f"(d[3]), "+f"(d[4]), "+f"(d[5]), "+f"(d[6]), "+f"(d[7]),
                   "+f"(d[8]), "+f"(d[9]), "+f"(d[10]), "+f"(d[11]), "+f"(d[12]), "+f"(d[13]), "+f"(d[14]), "+f"(d[15])
                 : "r"(da), "r"(db), "r"(acc), "n"(TA), "n"(0x40000040));
}
__device__ __forceinline__ void wg_fence() { asm volatile("wgmma.fence.sync.aligned;" ::: "memory"); }
__device__ __forceinline__ void wg_commit() { asm volatile("wgmma.commit_group.sync.aligned;" ::: "memory"); }
__device__ __forceinline__ void wg_wait0() { asm volatile("wgmma.wait_group.sync.aligned 0;" ::: "memory"); }
template <int N>
__device__ __forceinline__ void reg_fence(float (&d)[N]) {
#pragma unroll
    for (int i = 0; i < N; i++) asm volatile("" : "+f"(d[i])::"memory");
}
__device__ __forceinline__ void hold(unsigned t0, unsigned d) { while ((unsigned)clock() - t0 < d) {} }
__device__ __forceinline__ float gelu_tanh(float x) {
    float u = 0.7978845608028654f * (x + 0.044715f * x * x * x);
    float e = __expf(2.f * u);
    float th = 1.f - __fdividef(2.f, e + 1.f);
    return 0.5f * x * (1.f + th);
}

__device__ __forceinline__ void gemv_pair(uint32_t sb, uint32_t wbase, uint32_t red_off, uint32_t bar_idx, int warp, int lane, uint32_t rank) {
    const int mt = warp & 3, kh = warp >> 2, q = lane >> 3, g = lane >> 2, t = lane & 3;
    float c[4] = {0.f, 0.f, 0.f, 0.f};
    const uint32_t ab = sb + OFF_ACT + (g & 1) * ACT_PITCH + t * 4 + kh * 256;
    const int kr = kh * 128 + (q >> 1) * 8 + (lane & 7);
    const uint32_t wa = wbase + kr * 128 + (((2 * mt + (q & 1)) ^ (lane & 7)) << 4);
#pragma unroll
    for (int ks = 0; ks < 8; ks++) {
        uint32_t a[4];
        ldsm4t(a, wa + ks * 2048);
        mma16816(c, a, lds32(ab + ks * 32), lds32(ab + ks * 32 + 16));
    }
    const float v = (t & 2) ? ((t & 1) ? c[3] : c[2]) : ((t & 1) ? c[1] : c[0]);
    const uint32_t off = red_off + (((rank * 2 + kh) * 2 + (t & 1)) * 64 + mt * 16 + (t >> 1) * 8 + g) * 4;
    const uint32_t bar = OFF_BAR + bar_idx * 8;
    st_async32(mapa(sb + off, rank), v, mapa(sb + bar, rank));
    st_async32(mapa(sb + off, rank ^ 1), v, mapa(sb + bar, rank ^ 1));
}

__global__ void __cluster_dims__(2, 1, 1) __launch_bounds__(NTHR, 1)
fused_kernel(const __nv_bfloat16* __restrict__ gx, const __nv_bfloat16* __restrict__ gc,
             const __nv_bfloat16* __restrict__ gwmod, __nv_bfloat16* __restrict__ gout, Scratch* __restrict__ gs,
             const __grid_constant__ Maps maps) {
    extern __shared__ __align__(1024) unsigned char smem[];
    const uint32_t sb = smem_u32(smem);
    const int tid = threadIdx.x, lane = tid & 31;
    const int warp = __shfl_sync(0xffffffffu, tid >> 5, 0);
    const int cta = blockIdx.x;
    const uint32_t rank = cta & 1;
    const int hh = cta >> 2, pp = (cta >> 1) & 1;
    const int ab_ = cta >> 6, kb = (cta >> 1) & 31;
    const int kq = cta >> 5, cg = cta & 31;
    auto BAR = [&](int i) { return sb + OFF_BAR + i * 8; };

    if (warp < 8) {
        const __nv_bfloat16* src = gwmod + (size_t)tid * 3072 + cta * 8;
        asm volatile("cp.async.cg.shared.global [%0], [%1], 16;" ::"r"(sb + OFF_D + tid * 16), "l"(src) : "memory");
        asm volatile("cp.async.cg.shared.global [%0], [%1], 16;" ::"r"(sb + OFF_D + 4096 + tid * 16), "l"(src + 256 * 3072) : "memory");
        asm volatile("cp.async.commit_group;" ::: "memory");
    }

    if (warp == 8) {
        if (lane < 9) asm volatile("prefetch.tensormap [%0];" ::"l"(reinterpret_cast<const CUtensorMap*>(&maps) + lane) : "memory");
        if (elect_one()) {
#pragma unroll
            for (int i = B_WQ; i <= B_WD; i++) mbar_init(BAR(i), 1);
            mbar_init(BAR(B_QRED), 1);
            mbar_init(BAR(B_S0), 1); mbar_init(BAR(B_S1), 1); mbar_init(BAR(B_S2), 1); mbar_init(BAR(B_S3), 1);
            mbar_init(BAR(B_FREEB), 1); mbar_init(BAR(B_PEERC), 8); mbar_init(BAR(B_SFREE), 8);
            mbar_init(BAR(B_FREEA0), 16); mbar_init(BAR(B_FREEB2), 16); mbar_init(BAR(B_FREEA2), 16);
            asm volatile("fence.mbarrier_init.release.cluster;" ::: "memory");
            mbar_expect(BAR(B_WQ), 32768);
            mbar_expect(BAR(B_QRED), 2048);
            mbar_expect(BAR(B_S0), 8192); mbar_expect(BAR(B_S1), 8192); mbar_expect(BAR(B_S2), 8192); mbar_expect(BAR(B_S3), 8192);
        }
        __syncwarp();
        asm volatile("barrier.cluster.arrive.relaxed.aligned;" ::: "memory");
        if (elect_one()) {
            const unsigned t0 = (unsigned)clock();
            const unsigned slot = ((cta * 37) & 127) * STAG / 128;
            unsigned due = slot;
            unsigned rate = PACE1_NUM;
            auto pace = [&](unsigned kib) { while ((int)((unsigned)clock() - t0 - due) < 0) {} due += rate * kib / 16; };
            auto resync = [&]() { const unsigned now = (unsigned)clock() - t0; if ((int)(now - due) > 0) due = now; };
            auto ld128 = [&](uint32_t dst, const CUtensorMap* m, int c0, int r0, int rows, uint32_t bar) {
#pragma unroll 1
                for (int r = 0; r < rows; r += BOXK * 8) { pace(BOXK); tma2d(dst + r * 128, m, c0, r0 + r, bar); }
            };
            auto kvload = [&](int ch) {
                mbar_expect(BAR(B_KV0 + ch), 32768);
#pragma unroll 1
                for (int r = 0; r < 256; r += BOXK * 8) {
                    pace(BOXK);
                    tma2d(sb + OFF_A + ch * 32768 + r * 128, &maps.kv, (rank * 4 + (r >> 6)) * 64, ab_ * 8192 + kb * 256 + ch * 64 + (r & 63), BAR(B_KV0 + ch));
                }
            };
            ld128(sb + OFF_B, &maps.wq, hh * 128 + pp * 64, rank * 256, 256, BAR(B_WQ));
            mbar_expect(BAR(B_WUK), 32768);
            ld128(sb + OFF_C, &maps.wuk, hh * 128 + pp * 64, rank * 256, 256, BAR(B_WUK));
            rate = PACE_NUM;
            kvload(0);
            kvload(1);
            due += DSH - slot;
            kvload(2);
            kvload(3);
            due += slot;
            TLRECP(20);
            rate = PACE2_NUM;
            due += KVGAP;
            auto l_wuv = [&]() {
                mbar_wait(BAR(B_FREEB));
                mbar_expect(BAR(B_WUV), 32768);
                ld128(sb + OFF_B, &maps.wuv, hh * 128, (cta & 3) * 128, 128, BAR(B_WUV));
                ld128(sb + OFF_B + 16384, &maps.wuv, hh * 128 + 64, (cta & 3) * 128, 128, BAR(B_WUV));
            };
            auto ldmc = [&](uint32_t dst, const CUtensorMap* m, int c0, int r0, int half, uint32_t bar) {
                mbar_expect(bar, half * 128);
#pragma unroll 1
                for (int r = rank * half; r < rank * half + half; r += MBOX) { pace(MBOX / 16); tma2d_mc(dst + r * 64, m, c0, r0 + r, bar); }
            };
            auto l_wg = [&]() {
                if (cta < NFFN) { mbar_wait(BAR(B_FREEB2)); ldmc(sb + OFF_WG, &maps.wg, (cta >> 1) * 32, 0, 256, BAR(B_WG)); }
            };
            auto l_wu = [&]() { if (cta < NFFN) ldmc(sb + OFF_WU, &maps.wu, (cta >> 1) * 32, 0, 256, BAR(B_WU)); };
            auto l_wm = [&]() { ldmc(sb + OFF_WM2, &maps.wm, 1024 + (cta >> 1) * 32, 0, 256, BAR(B_WM2)); };
            auto l_wo = [&]() {
                mbar_wait(BAR(B_FREEA0));
                resync();
                ldmc(sb + OFF_WO, &maps.wo, (cg >> 1) * 32, kq * 1024, 512, BAR(B_WO));
            };
            auto l_wd = [&]() {
                if (cta < NFFN) {
                    mbar_expect(BAR(B_WD), 16384);
#pragma unroll 1
                    for (int j = 0; j < 8; j += BOXK / 2) { pace(BOXK); tma3d(sb + OFF_WD + j * 2048, &maps.wd, 0, cta * 16, j, BAR(B_WD)); }
                }
            };
            auto gap = [&]() { TLRECP(22); mbar_wait(BAR(B_FREEA2)); resync(); due += PAUSE; rate = PACE3_NUM; };
            l_wuv(); l_wo(); gap(); l_wm(); l_wg(); l_wu(); l_wd();
            TLRECP(24);
        }
        __syncwarp();
        asm volatile("barrier.cluster.wait.aligned;" ::: "memory");
        return;
    }

    const uint32_t epoch = ldr1(gs->epoch);

    if (warp == 9) {
        asm volatile("barrier.cluster.arrive.relaxed.aligned;" ::: "memory");
        const uint32_t tag = (epoch + 1) & 1;
        asm volatile("bar.sync 2, 288;" ::: "memory");
        asm volatile("barrier.cluster.wait.aligned;" ::: "memory");
        asm volatile("bar.sync 3, 288;" ::: "memory");
        const int q = lane >> 3, g = lane >> 2, t = lane & 3;
        uint32_t bq[16][4];
#pragma unroll
        for (int i = 0; i < 16; i++) ldsm4(bq[i], sb + OFF_SC + (lane & 1) * ACT_PITCH + q * 16 + i * 64);
        float c0[4] = {0.f, 0.f, 0.f, 0.f}, c1[4] = {0.f, 0.f, 0.f, 0.f}, c2[4] = {0.f, 0.f, 0.f, 0.f}, c3[4] = {0.f, 0.f, 0.f, 0.f};
        const int kr = (q >> 1) * 8 + (lane & 7);
        const uint32_t wa = sb + OFF_WM2 + kr * 64 + (((rank * 2 + (q & 1)) ^ ((kr >> 1) & 3)) << 4);
        mbar_wait(BAR(B_WM2));
#pragma unroll
        for (int i = 0; i < 16; i += 2) {
            uint32_t a0[4], a1[4], a2[4], a3[4];
            ldsm4t(a0, wa + i * 2048); ldsm4t(a1, wa + i * 2048 + 1024); ldsm4t(a2, wa + i * 2048 + 2048); ldsm4t(a3, wa + i * 2048 + 3072);
            mma16816(c0, a0, bq[i][0], bq[i][1]); mma16816(c1, a1, bq[i][2], bq[i][3]);
            mma16816(c2, a2, bq[i + 1][0], bq[i + 1][1]); mma16816(c3, a3, bq[i + 1][2], bq[i + 1][3]);
        }
#pragma unroll
        for (int i = 0; i < 4; i++) { c0[i] += c2[i]; c1[i] += c3[i]; }
        if (t < 2) {
            const uint32_t w = t ? pack2(c0[2] + c1[2], c0[3] + c1[3]) : pack2(c0[0] + c1[0], c0[1] + c1[1]);
            str1(gs->m2 + cta * 16 + t * 8 + g, tagw(w, tag));
        }
        return;
    }

    const int q4 = lane >> 3, g = lane >> 2, t = lane & 3;
    const uint32_t cw0 = ldr1(reinterpret_cast<const uint32_t*>(gc) + tid);
    const uint32_t cw1 = ldr1(reinterpret_cast<const uint32_t*>(gc) + 256 + tid);
    const uint32_t xw0 = ldr1(reinterpret_cast<const uint32_t*>(gx) + tid);
    const uint32_t xw1 = ldr1(reinterpret_cast<const uint32_t*>(gx) + 256 + tid);
    const float xh0 = __bfloat162float(gx[rank * 256 + tid]), xh1 = __bfloat162float(gx[512 + rank * 256 + tid]);
    {
        auto silu = [](float v) { return __fdividef(v, 1.f + __expf(-v)); };
        sts32(sb + OFF_SC + tid * 4, pack2(silu(bflo(cw0)), silu(bfhi(cw0))));
        sts32(sb + OFF_SC + ACT_PITCH + tid * 4, pack2(silu(bflo(cw1)), silu(bfhi(cw1))));
        float s0 = bflo(xw0) + bfhi(xw0), s1 = bflo(xw1) + bfhi(xw1);
        s0 = warp_sum(s0); s1 = warp_sum(s1);
        if (lane == 0) stsf2(sb + OFF_SM + warp * 8, s0, s1);
        if (tid < 32) { sts32(sb + OFF_SM + 256 + tid * 4, 0x80000000u); sts32(sb + OFF_SM + 384 + tid * 4, 0u); }
    }
    asm volatile("barrier.cluster.arrive.relaxed.aligned;" ::: "memory");
    asm volatile("cp.async.wait_group 0;" ::: "memory");
    asm volatile("bar.sync 2, 288;" ::: "memory");
    const uint32_t tag = (epoch + 1) & 1;
    TLREC(0);
    float mean0 = 0.f, mean1 = 0.f;
    {
#pragma unroll
        for (int w = 0; w < 8; w++) { float2 v = ldsf2(sb + OFF_SM + w * 8); mean0 += v.x; mean1 += v.y; }
        mean0 *= (1.f / 512.f); mean1 *= (1.f / 512.f);
        float c[4] = {0.f, 0.f, 0.f, 0.f};
        const uint32_t aa = sb + OFF_SC + (g & 1) * ACT_PITCH + warp * 128 + t * 4;
#pragma unroll
        for (int j = 0; j < 2; j++) {
            uint32_t b[4];
            ldsm4t(b, sb + OFF_D + (warp * 64 + j * 32 + lane) * 16);
            uint32_t a[4];
            a[0] = lds32(aa + j * 64); a[2] = lds32(aa + j * 64 + 16); a[1] = 0; a[3] = 0;
            mma16816(c, a, b[0], b[1]);
            a[0] = lds32(aa + j * 64 + 32); a[2] = lds32(aa + j * 64 + 48);
            mma16816(c, a, b[2], b[3]);
        }
        if (g < 2) stsf2(sb + OFF_RED + ((warp * 2 + g) * 8 + 2 * t) * 4, c[0], c[1]);
        float d0 = bflo(xw0) - mean0, d1 = bfhi(xw0) - mean0, d2 = bflo(xw1) - mean1, d3 = bfhi(xw1) - mean1;
        float v0 = warp_sum(d0 * d0 + d1 * d1), v1 = warp_sum(d2 * d2 + d3 * d3);
        if (lane == 0) stsf2(sb + OFF_SM + 64 + warp * 8, v0, v1);
    }
    bar_compute();
    if (tid < 8) {
        float s0 = 0.f, s1 = 0.f;
#pragma unroll
        for (int w = 0; w < 8; w++) { s0 += ldsf(sb + OFF_RED + (w * 16 + tid) * 4); s1 += ldsf(sb + OFF_RED + (w * 16 + 8 + tid) * 4); }
        str1(gs->e0 + cta * 8 + tid, tagw(pack2(s0, s1), tag));
    }
    TLREC(1);
    {
        const unsigned tw0 = (unsigned)clock();
        float v0 = 0.f, v1 = 0.f;
#pragma unroll
        for (int w = 0; w < 8; w++) { float2 v = ldsf2(sb + OFF_SM + 64 + w * 8); v0 += v.x; v1 += v.y; }
        const float r0 = rsqrtf(v0 * (1.f / 512.f) + 1e-5f), r1 = rsqrtf(v1 * (1.f / 512.f) + 1e-5f);
        const uint32_t* ps = gs->e0 + rank * 256 + tid;
        uint32_t sa, ca, n = 0;
        hold(tw0, D_E0);
        do { sa = ldr1(ps); ca = ldr1(ps + 512); } while (!(ok1(sa, tag) && ok1(ca, tag)) && ++n < SPIN_LIMIT);
        const float h0 = (xh0 - mean0) * r0 * (1.f + bflo(ca)) + bflo(sa);
        const float h1 = (xh1 - mean1) * r1 * (1.f + bfhi(ca)) + bfhi(sa);
        const uint32_t hw = pack2(h0, h1);
        sts16(sb + OFF_ACT + tid * 2, (uint16_t)(hw & 0xffff));
        sts16(sb + OFF_ACT + ACT_PITCH + tid * 2, (uint16_t)(hw >> 16));
    }
    asm volatile("barrier.cluster.wait.aligned;" ::: "memory");
    bar_compute();
    TLREC(2);
    mbar_wait(BAR(B_WQ));
    TLREC(3);
    gemv_pair(sb, sb + OFF_B, OFF_QRED, B_QRED, warp, lane, rank);
    mbar_wait(BAR(B_QRED));
    if (tid == 0) mbar_arrive(BAR(B_FREEB));
    if (tid < 64) {
        const int b = tid >> 5, k2 = tid & 31;
        float s0 = 0.f, s1 = 0.f;
#pragma unroll
        for (int s = 0; s < 4; s++) { float2 v = ldsf2(sb + OFF_QRED + ((s * 2 + b) * 64 + 2 * k2) * 4); s0 += v.x; s1 += v.y; }
        sts32(sb + OFF_ACT + b * ACT_PITCH + k2 * 4, pack2(s0, s1));
    }
    bar_compute();
    TLREC(4);
    mbar_wait(BAR(B_WUK));
    TLREC(5);
    {
        uint32_t bf[8];
        const uint32_t ab = sb + OFF_ACT + (g & 1) * ACT_PITCH + t * 4;
#pragma unroll
        for (int ks = 0; ks < 4; ks++) { bf[2 * ks] = lds32(ab + ks * 32); bf[2 * ks + 1] = lds32(ab + ks * 32 + 16); }
#pragma unroll
        for (int mi = 0; mi < 2; mi++) {
            const int m = (warp * 2 + mi) * 16 + (q4 & 1) * 8 + (lane & 7);
            float c[4] = {0.f, 0.f, 0.f, 0.f};
#pragma unroll
            for (int ks = 0; ks < 4; ks++) {
                uint32_t a[4];
                ldsm4(a, sb + OFF_C + m * 128 + (((2 * ks + (q4 >> 1)) ^ (lane & 7)) << 4));
                mma16816(c, a, bf[2 * ks], bf[2 * ks + 1]);
            }
            const float v = (t & 2) ? ((t & 1) ? c[3] : c[2]) : ((t & 1) ? c[1] : c[0]);
            const uint32_t w = pack2(v, 0.f);
            sts16(sb + OFF_RED + (t & 1) * 512 + ((warp * 2 + mi) * 16 + (t >> 1) * 8 + g) * 2, (uint16_t)(w & 0xffff));
        }
    }
    __syncwarp();
    if (lane == 0) {
        asm volatile("mbarrier.arrive.relaxed.cluster.shared::cluster.b64 _, [%0];" ::"r"(mapa(BAR(B_PEERC), rank ^ 1)) : "memory");
    }
    if (lane < 8) {
        const int b = lane >> 2;
        uint4 v = lds128(sb + OFF_RED + b * 512 + warp * 64 + (lane & 3) * 16);
        v.x = tagw(v.x, tag); v.y = tagw(v.y, tag); v.z = tagw(v.z, tag); v.w = tagw(v.w, tag);
        str4(gs->e1 + (((b * 2 + rank) * 2 + pp) * 32 + hh) * 128 + warp * 16 + (lane & 3) * 4, v);
    }
    TLREC(6);
    {
        const uint32_t* base = gs->e1 + ((ab_ * 2 + rank) * 2) * 32 * 128 + warp * 4 * 128;
        hold((unsigned)clock(), D_E1);
        uint4 v[8];
        uint32_t n = 0;
        bool ok;
#pragma unroll
        for (int j = 0; j < 8; j++) v[j] = ldr4(base + (j & 1) * 32 * 128 + (j >> 1) * 128 + lane * 4);
        do {
            ok = true;
#pragma unroll
            for (int j = 0; j < 8; j++)
                if (!ok4(v[j], tag)) { v[j] = ldr4(base + (j & 1) * 32 * 128 + (j >> 1) * 128 + lane * 4); ok = false; }
        } while (!ok && ++n < SPIN_LIMIT);
#pragma unroll
        for (int j = 0; j < 4; j++) {
            const uint4 a = v[2 * j], b = v[2 * j + 1];
            uint4 o;
            o.x = pack2(bflo(a.x) + bflo(b.x), bfhi(a.x) + bfhi(b.x));
            o.y = pack2(bflo(a.y) + bflo(b.y), bfhi(a.y) + bfhi(b.y));
            o.z = pack2(bflo(a.z) + bflo(b.z), bfhi(a.z) + bfhi(b.z));
            o.w = pack2(bflo(a.w) + bflo(b.w), bfhi(a.w) + bfhi(b.w));
            const int head = warp * 4 + j;
            sts128(sb + OFF_E + (lane >> 3) * 4096 + head * 128 + (((lane & 7) ^ (head & 7)) << 4), o);
        }
    }
    asm volatile("fence.proxy.async.shared::cta;" ::: "memory");
    mbar_wait(BAR(B_PEERC));
    asm volatile("bar.sync 3, 288;" ::: "memory");
    TLREC(7);
    const int wg = warp >> 2, wi = warp & 3, tw = tid & 127;
    {
        constexpr float SC = 0.08838834764831845f * 1.4426950408889634f;
        float o0[16], o1[16], lsum[8], mold[8];
        const uint32_t dA = desclo(sb + OFF_A), dD = desclo(sb + OFF_D), dE = desclo(sb + OFF_E);
#pragma unroll
        for (int i = 0; i < 8; i++) { lsum[i] = 0.f; mold[i] = 0.f; }
#pragma unroll
        for (int i = 0; i < 16; i++) { o0[i] = 0.f; o1[i] = 0.f; }
#pragma unroll 1
        for (int s = 0; s < 2; s++) {
            const int ch = 2 * s + wg;
            float sacc[16];
            mbar_wait(BAR(B_KV0 + ch));
            TLREC1(8 + (s == 0) * 2);
            wg_fence();
#pragma unroll
            for (int cb = 0; cb < 4; cb++)
#pragma unroll
                for (int ks = 0; ks < 4; ks++)
                    wgmma_n32<0>(sacc, dA + ch * 2048 + cb * 512 + ks * 2, dE + cb * 256 + ks * 2, (cb | ks) != 0);
            wg_commit();
            if (s) mbar_wait(BAR(B_SFREE));
            wg_wait0();
            reg_fence(sacc);
            TLREC1(26);
            {
                const uint32_t so = OFF_C + wg * 8192 + tw * 16;
                const uint32_t ra = mapa(sb + so, rank ^ 1), rb = mapa(BAR(B_S0 + ch), rank ^ 1);
#pragma unroll
                for (int j = 0; j < 4; j++) st_async128(ra + j * 2048, sacc[4 * j], sacc[4 * j + 1], sacc[4 * j + 2], sacc[4 * j + 3], rb);
                mbar_wait(BAR(B_S0 + ch));
#pragma unroll
                for (int j = 0; j < 4; j++) {
                    const float4 p = ldsf4(sb + so + j * 2048);
                    sacc[4 * j] = (sacc[4 * j] + p.x) * SC; sacc[4 * j + 1] = (sacc[4 * j + 1] + p.y) * SC;
                    sacc[4 * j + 2] = (sacc[4 * j + 2] + p.z) * SC; sacc[4 * j + 3] = (sacc[4 * j + 3] + p.w) * SC;
                }
                TLREC1(27);
                float mx[8];
#pragma unroll
                for (int j = 0; j < 4; j++) { mx[2 * j] = fmaxf(sacc[4 * j], sacc[4 * j + 2]); mx[2 * j + 1] = fmaxf(sacc[4 * j + 1], sacc[4 * j + 3]); }
                const bool u4 = lane & 16, u2 = lane & 8, u1 = lane & 4;
                float y[4], z[2];
#pragma unroll
                for (int i = 0; i < 4; i++) { const float keep = u4 ? mx[i + 4] : mx[i], send = u4 ? mx[i] : mx[i + 4]; y[i] = fmaxf(keep, __shfl_xor_sync(0xffffffffu, send, 16)); }
#pragma unroll
                for (int i = 0; i < 2; i++) { const float keep = u2 ? y[i + 2] : y[i], send = u2 ? y[i] : y[i + 2]; z[i] = fmaxf(keep, __shfl_xor_sync(0xffffffffu, send, 8)); }
                const float keep = u1 ? z[1] : z[0], send = u1 ? z[0] : z[1];
                const float r = fmaxf(keep, __shfl_xor_sync(0xffffffffu, send, 4));
                int key = __float_as_int(r);
                key = key >= 0 ? key : key ^ 0x7fffffff;
                const int head = 8 * (g >> 1) + 2 * t + (g & 1);
                asm volatile("red.shared.max.s32 [%0], %1;" ::"r"(sb + OFF_SM + 256 + head * 4), "r"(key) : "memory");
                if (s == 0 && lane == 0)
                    asm volatile("mbarrier.arrive.relaxed.cluster.shared::cluster.b64 _, [%0];" ::"r"(mapa(BAR(B_SFREE), rank ^ 1)) : "memory");
            }
            bar_compute();
            TLREC1(28);
            float mnew[8], alpha[8];
#pragma unroll
            for (int j = 0; j < 4; j++) {
                const float2 kk = ldsf2(sb + OFF_SM + 256 + (8 * j + 2 * t) * 4);
                int k0 = __float_as_int(kk.x), k1 = __float_as_int(kk.y);
                k0 = k0 >= 0 ? k0 : k0 ^ 0x7fffffff; k1 = k1 >= 0 ? k1 : k1 ^ 0x7fffffff;
                mnew[2 * j] = __int_as_float(k0); mnew[2 * j + 1] = __int_as_float(k1);
            }
            {
                uint32_t pk[8];
#pragma unroll
                for (int j = 0; j < 4; j++) {
                    const float p0 = ex2(sacc[4 * j] - mnew[2 * j]), p1 = ex2(sacc[4 * j + 1] - mnew[2 * j + 1]);
                    const float p2 = ex2(sacc[4 * j + 2] - mnew[2 * j]), p3 = ex2(sacc[4 * j + 3] - mnew[2 * j + 1]);
                    pk[2 * j] = pack2(p0, p1); pk[2 * j + 1] = pack2(p2, p3);
                }
                const int hrow = (q4 >> 1) * 8 + (lane & 7);
                const uint32_t pa = sb + OFF_D + wg * 4096 + hrow * 128 + (((2 * wi + (q4 & 1)) ^ (lane & 7)) << 4);
                stsm4t(pa, pk[0], pk[1], pk[2], pk[3]);
                stsm4t(pa + 2048, pk[4], pk[5], pk[6], pk[7]);
                asm volatile("fence.proxy.async.shared::cta;" ::: "memory");
#pragma unroll
                for (int j = 0; j < 4; j++) {
                    sacc[2 * j] = bflo(pk[2 * j]) + bflo(pk[2 * j + 1]);
                    sacc[2 * j + 1] = bfhi(pk[2 * j]) + bfhi(pk[2 * j + 1]);
                }
            }
            if (s) {
#pragma unroll
                for (int i = 0; i < 8; i++) { alpha[i] = ex2(mold[i] - mnew[i]); lsum[i] = lsum[i] * alpha[i] + sacc[i]; }
#pragma unroll
                for (int j = 0; j < 4; j++) {
                    o0[4 * j] *= alpha[2 * j]; o0[4 * j + 1] *= alpha[2 * j + 1]; o0[4 * j + 2] *= alpha[2 * j]; o0[4 * j + 3] *= alpha[2 * j + 1];
                    o1[4 * j] *= alpha[2 * j]; o1[4 * j + 1] *= alpha[2 * j + 1]; o1[4 * j + 2] *= alpha[2 * j]; o1[4 * j + 3] *= alpha[2 * j + 1];
                }
            } else {
#pragma unroll
                for (int i = 0; i < 8; i++) { mold[i] = mnew[i]; lsum[i] = sacc[i]; }
            }
            mbar_wait(BAR(B_KV0 + (ch ^ 1)));
            bar_compute();
            TLREC1(29);
            wg_fence();
#pragma unroll
            for (int ks = 0; ks < 8; ks++) {
                const uint32_t ka = dA + (s * 2 + (ks >> 2)) * 2048 + wg * 1024 + (ks & 3) * 128;
                const uint32_t db = dD + (ks >> 2) * 256 + (ks & 3) * 2;
                wgmma_n32<1>(o0, ka, db, 1);
                wgmma_n32<1>(o1, ka + 512, db, 1);
            }
            wg_commit();
            if (s == 1) {
                const bool u4 = lane & 16, u2 = lane & 8, u1 = lane & 4;
                float y[4], z[2];
#pragma unroll
                for (int i = 0; i < 4; i++) { const float keep = u4 ? lsum[i + 4] : lsum[i], send = u4 ? lsum[i] : lsum[i + 4]; y[i] = keep + __shfl_xor_sync(0xffffffffu, send, 16); }
#pragma unroll
                for (int i = 0; i < 2; i++) { const float keep = u2 ? y[i + 2] : y[i], send = u2 ? y[i] : y[i + 2]; z[i] = keep + __shfl_xor_sync(0xffffffffu, send, 8); }
                const float keep = u1 ? z[1] : z[0], send = u1 ? z[0] : z[1];
                const float r = keep + __shfl_xor_sync(0xffffffffu, send, 4);
                const int head = 8 * (g >> 1) + 2 * t + (g & 1);
                asm volatile("red.shared.add.f32 [%0], %1;" ::"r"(sb + OFF_SM + 384 + head * 4), "f"(r) : "memory");
            }
            wg_wait0();
            reg_fence(o0); reg_fence(o1);
            if (lane == 0) {
                mbar_arrive(BAR(s ? B_FREEA2 : B_FREEA0));
                asm volatile("mbarrier.arrive.relaxed.cluster.shared::cluster.b64 _, [%0];" ::"r"(mapa(BAR(s ? B_FREEA2 : B_FREEA0), rank ^ 1)) : "memory");
            }
            TLREC1(9 + (s == 0) * 21);
        }
        TLREC(31);
        {
            const int hrow = (q4 >> 1) * 8 + (lane & 7);
#pragma unroll
            for (int mi = 0; mi < 2; mi++) {
                const float(&o)[16] = mi ? o1 : o0;
                const int chunk = (wg * 2 + mi) * 8 + wi * 2 + (q4 & 1);
                const uint32_t a = sb + OFF_E + hrow * 512 + ((chunk ^ (lane & 7)) << 4);
                stsm4t(a, pack2(o[0], o[1]), pack2(o[2], o[3]), pack2(o[4], o[5]), pack2(o[6], o[7]));
                stsm4t(a + 16 * 512, pack2(o[8], o[9]), pack2(o[10], o[11]), pack2(o[12], o[13]), pack2(o[14], o[15]));
            }
        }
    }
    bar_compute();
    TLREC(11);
    {
        const int part = ab_ * 32 + kb;
        if (lane < 8) {
            const int head = warp * 4 + (lane >> 1);
            int k = (int)lds32(sb + OFF_SM + 256 + head * 4);
            k = k >= 0 ? k : k ^ 0x7fffffff;
            const uint32_t m = tagw((uint32_t)k, tag), l = tagw(lds32(sb + OFF_SM + 384 + head * 4), tag);
            str4(gs->ml + ((head * 2 + rank) * 64 + part) * 8 + (lane & 1) * 4, make_uint4(m, l, m, l));
        }
#pragma unroll
        for (int j = 0; j < 4; j++) {
            const int head = warp * 4 + j;
            uint4 v = lds128(sb + OFF_E + head * 512 + ((lane ^ (head & 7)) << 4));
            v.x = tagw(v.x, tag); v.y = tagw(v.y, tag); v.z = tagw(v.z, tag); v.w = tagw(v.w, tag);
            str4(gs->e2 + ((head * 4 + rank * 2 + (lane >> 4)) * 64 + part) * 64 + (lane & 15) * 4, v);
        }
        TLREC(21);
    }
    TLREC(12);
    uint32_t wf[8][4];
    {
        const unsigned tw0 = (unsigned)clock();
        const int b = warp >> 2, ph = warp & 1;
        const uint32_t* pml = gs->ml + ((hh * 2 + pp) * 64 + b * 32 + lane) * 8;
        const uint32_t* pd = gs->e2 + ((hh * 4 + (cta & 3)) * 64 + b * 32 + ph * 16 + q4) * 64 + (warp & 2) * 16 + (lane & 7) * 4;
        uint2 ml = make_uint2(~tag, ~tag);
        uint4 v[4];
#pragma unroll
        for (int j = 0; j < 4; j++) v[j] = make_uint4(~tag, ~tag, ~tag, ~tag);
        mbar_wait(BAR(B_WUV));
        {
            const int kr = (q4 >> 1) * 8 + (lane & 7);
            const uint32_t wa = sb + OFF_B + (warp >> 2) * 16384 + kr * 128 + (((2 * (warp & 3) + (q4 & 1)) ^ (lane & 7)) << 4);
#pragma unroll
            for (int ks = 0; ks < 8; ks++) ldsm4t(wf[ks], wa + ks * 2048);
            uint32_t dep;
            asm volatile("popc.b32 %0, %1;" : "=r"(dep) : "r"(wf[0][0] ^ wf[1][0] ^ wf[2][0] ^ wf[3][0] ^ wf[4][0] ^ wf[5][0] ^ wf[6][0] ^ wf[7][0]));
            dep = __shfl_sync(0xffffffffu, dep, 0) >> 6;
            if (lane == 0) {
                mbar_arrive(BAR(B_FREEB2) + dep);
                asm volatile("mbarrier.arrive.relaxed.cluster.shared::cluster.b64 _, [%0];" ::"r"(mapa(BAR(B_FREEB2) + dep, rank ^ 1)) : "memory");
            }
        }
        hold(tw0, D_E2);
        uint32_t n = 0;
        bool ok;
        do {
            if (!ok2(ml, tag)) ml = ldr2(pml);
#pragma unroll
            for (int j = 0; j < 4; j++) if (!ok4(v[j], tag)) v[j] = ldr4(pd + j * 4 * 64);
            ok = ok2(ml, tag) && ok4(v[0], tag) && ok4(v[1], tag) && ok4(v[2], tag) && ok4(v[3], tag);
        } while (!ok && ++n < SPIN_LIMIT);
        __syncwarp();
        const float m = __uint_as_float(ml.x);
        float M = m;
#pragma unroll
        for (int o = 16; o; o >>= 1) M = fmaxf(M, __shfl_xor_sync(0xffffffffu, M, o));
        float w = ex2(m - M);
        const float L = warp_sum(w * __uint_as_float(ml.y));
        float a[8];
#pragma unroll
        for (int i = 0; i < 8; i++) a[i] = 0.f;
#pragma unroll
        for (int j = 0; j < 4; j++) {
            const float wj = __shfl_sync(0xffffffffu, w, ph * 16 + j * 4 + q4);
            a[0] += wj * bflo(v[j].x); a[1] += wj * bfhi(v[j].x); a[2] += wj * bflo(v[j].y); a[3] += wj * bfhi(v[j].y);
            a[4] += wj * bflo(v[j].z); a[5] += wj * bfhi(v[j].z); a[6] += wj * bflo(v[j].w); a[7] += wj * bfhi(v[j].w);
        }
        const bool u4 = lane & 16, u2 = lane & 8;
        float y[4], z[2];
#pragma unroll
        for (int i = 0; i < 4; i++) { const float keep = u4 ? a[i + 4] : a[i], send = u4 ? a[i] : a[i + 4]; y[i] = keep + __shfl_xor_sync(0xffffffffu, send, 16); }
#pragma unroll
        for (int i = 0; i < 2; i++) { const float keep = u2 ? y[i + 2] : y[i], send = u2 ? y[i] : y[i + 2]; z[i] = keep + __shfl_xor_sync(0xffffffffu, send, 8); }
        const float rl = __fdividef(1.f, L);
        sts32(sb + OFF_ACT + (ph * 2 + b) * 272 + ((warp & 2) * 32 + (lane & 7) * 8 + q4 * 2) * 2, pack2(z[0] * rl, z[1] * rl));
    }
    bar_compute();
    TLREC(13);
    {
        float c[4] = {0.f, 0.f, 0.f, 0.f}, c2[4] = {0.f, 0.f, 0.f, 0.f};
        const uint32_t ab = sb + OFF_ACT + (lane & 3) * 272 + q4 * 16;
#pragma unroll
        for (int ks = 0; ks < 8; ks += 2) {
            uint32_t bq[4];
            ldsm4(bq, ab + ks * 32);
            mma16816(c, wf[ks], bq[0], bq[1]);
            mma16816(c2, wf[ks + 1], bq[2], bq[3]);
        }
        float x = (t & 2) ? c[2] + c2[2] : c[0] + c2[0], y = (t & 2) ? c[3] + c2[3] : c[1] + c2[1];
        x += __shfl_xor_sync(0xffffffffu, x, 1); y += __shfl_xor_sync(0xffffffffu, y, 1);
        if (!(t & 1)) str1(gs->x1 + (cta & 3) * 4096 + hh * 128 + warp * 16 + (t >> 1) * 8 + g, tagw(pack2(x, y), tag));
    }
    TLREC(14);
    {
        const unsigned tw0 = (unsigned)clock();
        const uint32_t* px = gs->x1 + kq * 1024 + tid * 4;
        mbar_wait(BAR(B_WO));
        {
            const int kr = warp * 128 + (q4 >> 1) * 8 + (lane & 7);
            const uint32_t wa = sb + OFF_WO + kr * 64 + (((rank * 2 + (q4 & 1)) ^ ((kr >> 1) & 3)) << 4);
#pragma unroll
            for (int ks = 0; ks < 8; ks++) ldsm4t(wf[ks], wa + ks * 1024);
        }
        uint4 u[4];
        uint32_t n = 0;
        bool ok;
#pragma unroll
        for (int j = 0; j < 4; j++) u[j] = make_uint4(~tag, ~tag, ~tag, ~tag);
        hold(tw0, D_X1);
        do {
#pragma unroll
            for (int j = 0; j < 4; j++) if (!ok4(u[j], tag)) u[j] = ldr4(px + j * 4096);
            ok = ok4(u[0], tag) && ok4(u[1], tag) && ok4(u[2], tag) && ok4(u[3], tag);
        } while (!ok && ++n < SPIN_LIMIT);
        const uint32_t da = sb + OFF_D + tid * 8;
        sts64(da, pack2((bflo(u[0].x) + bflo(u[1].x)) + (bflo(u[2].x) + bflo(u[3].x)), (bflo(u[0].y) + bflo(u[1].y)) + (bflo(u[2].y) + bflo(u[3].y))),
              pack2((bflo(u[0].z) + bflo(u[1].z)) + (bflo(u[2].z) + bflo(u[3].z)), (bflo(u[0].w) + bflo(u[1].w)) + (bflo(u[2].w) + bflo(u[3].w))));
        sts64(da + ACTL_PITCH, pack2((bfhi(u[0].x) + bfhi(u[1].x)) + (bfhi(u[2].x) + bfhi(u[3].x)), (bfhi(u[0].y) + bfhi(u[1].y)) + (bfhi(u[2].y) + bfhi(u[3].y))),
              pack2((bfhi(u[0].z) + bfhi(u[1].z)) + (bfhi(u[2].z) + bfhi(u[3].z)), (bfhi(u[0].w) + bfhi(u[1].w)) + (bfhi(u[2].w) + bfhi(u[3].w))));
    }
    uint2 ga = ldr2(gs->m2 + 2 * tid), sbv = ldr2(gs->m2 + 512 + 2 * tid), cbv = ldr2(gs->m2 + 1024 + 2 * tid);
    uint32_t gbw = ldr1(gs->m2 + 1536 + (cta & 63) * 8 + (tid & 7));
    __syncwarp();
    TLREC(15);
    {
        float c[4] = {0.f, 0.f, 0.f, 0.f}, c2[4] = {0.f, 0.f, 0.f, 0.f};
        const uint32_t ab = sb + OFF_D + (lane & 1) * ACTL_PITCH + warp * 256 + q4 * 16;
#pragma unroll
        for (int ks = 0; ks < 8; ks += 2) {
            uint32_t bq[4];
            ldsm4(bq, ab + ks * 32);
            mma16816(c, wf[ks], bq[0], bq[1]);
            mma16816(c2, wf[ks + 1], bq[2], bq[3]);
        }
        if (t < 2) stsf2(sb + OFF_RED + (warp * 16 + t * 8 + g) * 8, t ? c[2] + c2[2] : c[0] + c2[0], t ? c[3] + c2[3] : c[1] + c2[1]);
    }
    bar_compute();
    if (tid < 16) {
        float s0 = 0.f, s1 = 0.f;
#pragma unroll
        for (int w = 0; w < 8; w++) { float2 v = ldsf2(sb + OFF_RED + (w * 16 + tid) * 8); s0 += v.x; s1 += v.y; }
        str1(gs->x2 + kq * 512 + cg * 16 + tid, tagw(pack2(s0, s1), tag));
    }
    TLREC(16);
    bool pre;
    const uint32_t wgu = sb + ((warp >> 2) ? OFF_WU : OFF_WG) + ((warp & 3) * 128 + (q4 >> 1) * 8 + (lane & 7)) * 64 + (((rank * 2 + (q4 & 1)) ^ ((lane >> 1) & 3)) << 4);
    {
        const unsigned tw0 = (unsigned)clock();
        uint32_t n = 0;
        while (!(ok2(ga, tag) && ok2(sbv, tag) && ok2(cbv, tag) && ok1(gbw, tag)) && ++n < SPIN_LIMIT) {
            ga = ldr2(gs->m2 + 2 * tid); sbv = ldr2(gs->m2 + 512 + 2 * tid); cbv = ldr2(gs->m2 + 1024 + 2 * tid);
            gbw = ldr1(gs->m2 + 1536 + (cta & 63) * 8 + (tid & 7));
        }
        const float k00 = 1.f + bflo(cbv.x), k01 = 1.f + bflo(cbv.y), k10 = 1.f + bfhi(cbv.x), k11 = 1.f + bfhi(cbv.y);
        sts32(sb + OFF_E + 2 * ACT_PITCH + tid * 4, pack2(k00, k01));
        sts32(sb + OFF_E + 3 * ACT_PITCH + tid * 4, pack2(k10, k11));
        sts32(sb + OFF_E + 4 * ACT_PITCH + tid * 4, __byte_perm(sbv.x, sbv.y, 0x5410));
        sts32(sb + OFF_E + 5 * ACT_PITCH + tid * 4, __byte_perm(sbv.x, sbv.y, 0x7632));
        uint2 p[4];
        bool ok;
        n = 0;
        pre = cta < NFFN && __all_sync(0xffffffffu, mbar_test(BAR((warp >> 2) ? B_WU : B_WG)));
        if (pre) {
#pragma unroll
            for (int ks = 0; ks < 8; ks++) ldsm4t(wf[ks], wgu + ks * 1024);
        }
#pragma unroll
        for (int j = 0; j < 4; j++) p[j] = make_uint2(~tag, ~tag);
        hold(tw0, D_X2);
        do {
#pragma unroll
            for (int j = 0; j < 4; j++) if (!ok2(p[j], tag)) p[j] = ldr2(gs->x2 + j * 512 + 2 * tid);
            ok = ok2(p[0], tag) && ok2(p[1], tag) && ok2(p[2], tag) && ok2(p[3], tag);
        } while (!ok && ++n < SPIN_LIMIT);
        const float a00 = (bflo(p[0].x) + bflo(p[1].x)) + (bflo(p[2].x) + bflo(p[3].x));
        const float a10 = (bfhi(p[0].x) + bfhi(p[1].x)) + (bfhi(p[2].x) + bfhi(p[3].x));
        const float a01 = (bflo(p[0].y) + bflo(p[1].y)) + (bflo(p[2].y) + bflo(p[3].y));
        const float a11 = (bfhi(p[0].y) + bfhi(p[1].y)) + (bfhi(p[2].y) + bfhi(p[3].y));
        const float y00 = bflo(xw0) + bflo(ga.x) * a00, y01 = bfhi(xw0) + bflo(ga.y) * a01;
        const float y10 = bflo(xw1) + bfhi(ga.x) * a10, y11 = bfhi(xw1) + bfhi(ga.y) * a11;
        sts32(sb + OFF_E + tid * 4, pack2(y00 * k00, y01 * k01));
        sts32(sb + OFF_E + ACT_PITCH + tid * 4, pack2(y10 * k10, y11 * k11));
        if ((tid >> 2) == (cta & 63)) stsf2(sb + OFF_SM + 192 + (tid & 3) * 8, ab_ ? y10 : y00, ab_ ? y11 : y01);
        const bool u4 = lane & 16, u2 = lane & 8;
        const float s0 = y00 + y01, s1 = y10 + y11, q0 = y00 * y00 + y01 * y01, q1 = y10 * y10 + y11 * y11;
        const float r0 = (u4 ? q0 : s0) + __shfl_xor_sync(0xffffffffu, u4 ? s0 : q0, 16);
        const float r1 = (u4 ? q1 : s1) + __shfl_xor_sync(0xffffffffu, u4 ? s1 : q1, 16);
        float r = (u2 ? r1 : r0) + __shfl_xor_sync(0xffffffffu, u2 ? r0 : r1, 8);
        r += __shfl_xor_sync(0xffffffffu, r, 4); r += __shfl_xor_sync(0xffffffffu, r, 2); r += __shfl_xor_sync(0xffffffffu, r, 1);
        if (!(lane & 7)) stsf(sb + OFF_SM + warp * 16 + (lane >> 3) * 4, r);
    }
    bar_compute();
    TLREC(17);
    if (cta < NFFN) {
        if (!pre) {
            mbar_wait(BAR((warp >> 2) ? B_WU : B_WG));
#pragma unroll
            for (int ks = 0; ks < 8; ks++) ldsm4t(wf[ks], wgu + ks * 1024);
        }
        {
            float c[4] = {0.f, 0.f, 0.f, 0.f}, c2[4] = {0.f, 0.f, 0.f, 0.f};
            const int br = lane & 7;
            const uint32_t ab = sb + OFF_E + (br < 6 ? br : br - 6) * ACT_PITCH + (warp & 3) * 256 + q4 * 16;
#pragma unroll
            for (int ks = 0; ks < 8; ks += 2) {
                uint32_t bq[4];
                ldsm4(bq, ab + ks * 32);
                mma16816(c, wf[ks], bq[0], bq[1]);
                mma16816(c2, wf[ks + 1], bq[2], bq[3]);
            }
            float4 st = make_float4(0.f, 0.f, 0.f, 0.f);
#pragma unroll
            for (int w = 0; w < 8; w++) { const float4 v = ldsf4(sb + OFF_SM + w * 16); st.x += v.x; st.y += v.y; st.z += v.z; st.w += v.w; }
            const float m0 = st.x * (1.f / 512.f), m1 = st.y * (1.f / 512.f);
            const float r0 = rsqrtf(fmaxf(st.z * (1.f / 512.f) - m0 * m0, 0.f) + 1e-5f), r1 = rsqrtf(fmaxf(st.w * (1.f / 512.f) - m1 * m1, 0.f) + 1e-5f);
            const float f0 = t == 0 ? r0 : (t == 1 ? -r0 * m0 : (t == 2 ? 1.f : 0.f));
            const float f1 = t == 0 ? r1 : (t == 1 ? -r1 * m1 : (t == 2 ? 1.f : 0.f));
            const float e0 = (c[0] + c2[0]) * f0, e1 = (c[1] + c2[1]) * f1, e2 = (c[2] + c2[2]) * f0, e3 = (c[3] + c2[3]) * f1;
            const bool w2 = t & 2, w1 = t & 1;
            const float h0 = (w2 ? e2 : e0) + __shfl_xor_sync(0xffffffffu, w2 ? e0 : e2, 2);
            const float h1 = (w2 ? e3 : e1) + __shfl_xor_sync(0xffffffffu, w2 ? e1 : e3, 2);
            const float v = (w1 ? h1 : h0) + __shfl_xor_sync(0xffffffffu, w1 ? h0 : h1, 1);
            stsf(sb + OFF_RED + ((warp * 2 + (t & 1)) * 16 + (t >> 1) * 8 + g) * 4, v);
        }
        mbar_wait(BAR(B_WD));
#pragma unroll
        for (int mi = 0; mi < 4; mi++)
            ldsm4t(wf[mi], sb + OFF_WD + warp * 2048 + ((q4 >> 1) * 8 + (lane & 7)) * 128 + (((2 * mi + (q4 & 1)) ^ (lane & 7)) << 4));
        bar_compute();
        uint32_t b0, b1;
        {
            float gv[4] = {0.f, 0.f, 0.f, 0.f}, uv[4] = {0.f, 0.f, 0.f, 0.f};
            const uint32_t ra = sb + OFF_RED + ((g & 1) * 16 + 2 * t) * 4;
#pragma unroll
            for (int s = 0; s < 4; s++) {
                const float2 x0 = ldsf2(ra + s * 128), x1 = ldsf2(ra + s * 128 + 32);
                const float2 y0 = ldsf2(ra + 512 + s * 128), y1 = ldsf2(ra + 512 + s * 128 + 32);
                gv[0] += x0.x; gv[1] += x0.y; gv[2] += x1.x; gv[3] += x1.y;
                uv[0] += y0.x; uv[1] += y0.y; uv[2] += y1.x; uv[3] += y1.y;
            }
            b0 = pack2(gelu_tanh(gv[0]) * uv[0], gelu_tanh(gv[1]) * uv[1]);
            b1 = pack2(gelu_tanh(gv[2]) * uv[2], gelu_tanh(gv[3]) * uv[3]);
        }
#pragma unroll
        for (int mi = 0; mi < 4; mi++) {
            float c[4] = {0.f, 0.f, 0.f, 0.f};
            mma16816(c, wf[mi], b0, b1);
            const float v = (t & 2) ? ((t & 1) ? c[3] : c[2]) : ((t & 1) ? c[1] : c[0]);
            const int cons = (t & 1) * 64 + warp * 8 + mi * 2 + (t >> 1);
            str1(gs->e4 + (cons * NFFN + cta) * 8 + g, tagw(__float_as_uint(v), tag));
        }
    }
    TLREC(18);
    if (warp < 7) {
        const uint32_t* pe = gs->e4 + cta * NFFN * 8 + tid * 4;
        uint4 v;
        uint32_t n = 0;
        hold((unsigned)clock(), D_E4);
        do { v = ldr4(pe); } while (!ok4(v, tag) && ++n < SPIN_LIMIT);
        __syncwarp();
        float f0 = __uint_as_float(v.x), f1 = __uint_as_float(v.y), f2 = __uint_as_float(v.z), f3 = __uint_as_float(v.w);
#pragma unroll
        for (int o = 2; o <= 16; o <<= 1) {
            f0 += __shfl_xor_sync(0xffffffffu, f0, o); f1 += __shfl_xor_sync(0xffffffffu, f1, o);
            f2 += __shfl_xor_sync(0xffffffffu, f2, o); f3 += __shfl_xor_sync(0xffffffffu, f3, o);
        }
        if (lane < 2) { stsf2(sb + OFF_CRED + warp * 32 + lane * 16, f0, f1); stsf2(sb + OFF_CRED + warp * 32 + lane * 16 + 8, f2, f3); }
    }
    bar_compute();
    if (tid < 8) {
        float s = 0.f;
#pragma unroll
        for (int w = 0; w < 7; w++) s += ldsf(sb + OFF_CRED + w * 32 + tid * 4);
        const float gb = ab_ ? bfhi(gbw) : bflo(gbw);
        gout[cta * 8 + tid] = __float2bfloat16(ldsf(sb + OFF_SM + 192 + tid * 4) + gb * s);
        if (cta == 0 && tid == 0) str1(gs->epoch, epoch + 1);
    }
    TLREC(19);
}

typedef CUresult (*EncodeFn)(CUtensorMap*, CUtensorMapDataType, cuuint32_t, void*, const cuuint64_t*, const cuuint64_t*,
                             const cuuint32_t*, const cuuint32_t*, CUtensorMapInterleave, CUtensorMapSwizzle,
                             CUtensorMapL2promotion, CUtensorMapFloatOOBfill);

void enc2d(EncodeFn f, CUtensorMap* m, const void* p, uint64_t cols, uint64_t rows, uint32_t bc, uint32_t br, CUtensorMapSwizzle sw) {
    cuuint64_t dims[2] = {cols, rows};
    cuuint64_t strides[1] = {cols * 2};
    cuuint32_t box[2] = {bc, br}, es[2] = {1, 1};
    f(m, CU_TENSOR_MAP_DATA_TYPE_BFLOAT16, 2, const_cast<void*>(p), dims, strides, box, es, CU_TENSOR_MAP_INTERLEAVE_NONE, sw,
      CU_TENSOR_MAP_L2_PROMOTION_NONE, CU_TENSOR_MAP_FLOAT_OOB_FILL_NONE);
}
void enc3d(EncodeFn f, CUtensorMap* m, const void* p, uint64_t rows, uint32_t br, uint32_t bb) {
    cuuint64_t dims[3] = {64, rows, 8};
    cuuint64_t strides[2] = {1024, 128};
    cuuint32_t box[3] = {64, br, bb}, es[3] = {1, 1, 1};
    f(m, CU_TENSOR_MAP_DATA_TYPE_BFLOAT16, 3, const_cast<void*>(p), dims, strides, box, es, CU_TENSOR_MAP_INTERLEAVE_NONE,
      CU_TENSOR_MAP_SWIZZLE_128B, CU_TENSOR_MAP_L2_PROMOTION_NONE, CU_TENSOR_MAP_FLOAT_OOB_FILL_NONE);
}

}

extern "C" void kernel_launch(void* const* d_in, const int* in_sizes, int n_in, void* d_out, int out_size) {
    (void)in_sizes; (void)n_in; (void)out_size;
    static EncodeFn enc = nullptr;
    static Scratch* scratch = nullptr;
    if (!enc) {
        void* fn = nullptr;
        cudaDriverEntryPointQueryResult qr;
        cudaGetDriverEntryPoint("cuTensorMapEncodeTiled", &fn, cudaEnableDefault, &qr);
        enc = (EncodeFn)fn;
        cudaGetSymbolAddress((void**)&scratch, g_s);
        cudaFuncSetAttribute(fused_kernel, cudaFuncAttributeMaxDynamicSharedMemorySize, SMEM_BYTES);
    }
    Maps m;
    enc2d(enc, &m.wq, d_in[2], 4096, 512, 64, BOXK * 8, CU_TENSOR_MAP_SWIZZLE_128B);
    enc2d(enc, &m.wuk, d_in[3], 4096, 512, 64, BOXK * 8, CU_TENSOR_MAP_SWIZZLE_128B);
    enc2d(enc, &m.wuv, d_in[4], 4096, 512, 64, BOXK * 8, CU_TENSOR_MAP_SWIZZLE_128B);
    enc2d(enc, &m.kv, d_in[1], 512, 16384, 64, BOXK * 8, CU_TENSOR_MAP_SWIZZLE_128B);
    enc2d(enc, &m.wo, d_in[5], 512, 4096, 32, MBOX, CU_TENSOR_MAP_SWIZZLE_64B);
    enc2d(enc, &m.wm, d_in[11], 3072, 512, 32, MBOX, CU_TENSOR_MAP_SWIZZLE_64B);
    enc2d(enc, &m.wg, d_in[7], 1792, 512, 32, MBOX, CU_TENSOR_MAP_SWIZZLE_64B);
    enc2d(enc, &m.wu, d_in[8], 1792, 512, 32, MBOX, CU_TENSOR_MAP_SWIZZLE_64B);
    enc3d(enc, &m.wd, d_in[9], 1792, 16, BOXK / 2);
    fused_kernel<<<NCTA, NTHR, SMEM_BYTES>>>((const __nv_bfloat16*)d_in[0], (const __nv_bfloat16*)d_in[10],
                                             (const __nv_bfloat16*)d_in[11], (__nv_bfloat16*)d_out, scratch, m);
}
```
